```python
import torch

def _softmax(x, axis=-1):
    return torch.softmax(x, dim=axis)
def _gelu(x):
    return torch.nn.functional.gelu(x, approximate="tanh")
def _silu(x):
    return torch.nn.functional.silu(x)
def _sigmoid(x):
    return torch.sigmoid(x)
def _layernorm(x, axis=-1, eps=1e-5):
    m = x.mean(dim=axis, keepdim=True)
    v = x.var(dim=axis, keepdim=True, unbiased=False)
    return (x - m) / torch.sqrt(v + eps)
def _scatter_add(tgt, idx, src, axis=0):
    return tgt.clone().index_add_(axis, idx, src)
def _segment_sum(src, seg, n):
    out = torch.zeros((n,) + src.shape[1:], dtype=src.dtype)
    return out.index_add_(0, seg, src)
def _pad(x, pw):
    flat = tuple(v for pair in reversed(pw) for v in pair)
    return torch.nn.functional.pad(x, flat)

kernel_name = 'concat_heads__sliding_block_cached__sliding_block_cached__decode'

def setup_inputs():

    _w = (lambda a: (lambda t: t.to(torch.bfloat16) if t.is_floating_point() else t)(torch.as_tensor(a)))
    def _A_setup():
        B, Sq, D = 4, 1, 640
        Hq, Hkv, Sk, Dh = 32, 32, 8192, 128
        assert Hq % Hkv == 0, (Hq, Hkv)
        return {
            "x": _w((lambda *s: torch.randn(*s, dtype=torch.bfloat16) * 0.8)(B, Sq, D)),
            "k_cache": _w((lambda *s: torch.randn(*s, dtype=torch.bfloat16) * 0.8)(B, Hkv, Sk, Dh)),
            "v_cache": _w((lambda *s: torch.randn(*s, dtype=torch.bfloat16) * 0.05)(B, Hkv, Sk, Dh)),
            "wq": _w((lambda *s: torch.randn(*s, dtype=torch.bfloat16) * 0.8)(D, Hq * Dh) * (D ** -0.5)),
            "wo": _w((lambda *s: torch.randn(*s, dtype=torch.bfloat16) * 0.05)(Hq * Dh, D) * ((Hq * Dh) ** -0.5)),
        }
    _A_in = _A_setup()

    def _B_setup():
        B, Sq, D = 4, 1, 640
        Hq, Hkv, Sk, Dh = 32, 32, 8192, 128
        assert Hq % Hkv == 0, (Hq, Hkv)
        return {
            "x": _w((lambda *s: torch.randn(*s, dtype=torch.bfloat16) * 0.8)(B, Sq, D)),
            "k_cache": _w((lambda *s: torch.randn(*s, dtype=torch.bfloat16) * 0.8)(B, Hkv, Sk, Dh)),
            "v_cache": _w((lambda *s: torch.randn(*s, dtype=torch.bfloat16) * 0.05)(B, Hkv, Sk, Dh)),
            "wq": _w((lambda *s: torch.randn(*s, dtype=torch.bfloat16) * 0.8)(D, Hq * Dh) * (D ** -0.5)),
            "wo": _w((lambda *s: torch.randn(*s, dtype=torch.bfloat16) * 0.05)(Hq * Dh, D) * ((Hq * Dh) ** -0.5)),
        }
    _B_in = _B_setup()

    return {
        "A_x": _A_in["x"],
        "A_k_cache": _A_in["k_cache"],
        "A_v_cache": _A_in["v_cache"],
        "A_wq": _A_in["wq"],
        "A_wo": _A_in["wo"],
        "B_x": _B_in["x"],
        "B_k_cache": _B_in["k_cache"],
        "B_v_cache": _B_in["v_cache"],
        "B_wq": _B_in["wq"],
        "B_wo": _B_in["wo"],
    }

def reference(A_x, A_k_cache, A_v_cache, A_wq, A_wo, B_x, B_k_cache, B_v_cache, B_wq, B_wo):
    def _A_ref(x, k_cache, v_cache, wq, wo):
        B, Sq, D = x.shape
        Hq, Dh = 32, 128
        Hkv, Sk = k_cache.shape[1], k_cache.shape[2]
        W = min(4096, max(256, Sk // 4))
        rep = Hq // Hkv
        q = (lambda x, *d: x.permute(*d))((x @ wq).reshape(B, Sq, Hq, Dh), 0, 2, 1, 3)
        k = (lambda x, n, axis: torch.repeat_interleave(x, n, dim=axis))(k_cache[:, :, Sk - W:, :], rep, axis=1)
        v = (lambda x, n, axis: torch.repeat_interleave(x, n, dim=axis))(v_cache[:, :, Sk - W:, :], rep, axis=1)
        scores = torch.einsum("bhqd,bhkd->bhqk", q, k) * (Dh ** -0.5)
        p = _softmax(scores, axis=-1)
        o = torch.einsum("bhqk,bhkd->bhqd", p, v)
        return (lambda x, *d: x.permute(*d))(o, 0, 2, 1, 3).reshape(B, Sq, Hq * Dh) @ wo

    def _B_ref(x, k_cache, v_cache, wq, wo):
        B, Sq, D = x.shape
        Hq, Dh = 32, 128
        Hkv, Sk = k_cache.shape[1], k_cache.shape[2]
        W = min(4096, max(256, Sk // 4))
        rep = Hq // Hkv
        q = (lambda x, *d: x.permute(*d))((x @ wq).reshape(B, Sq, Hq, Dh), 0, 2, 1, 3)
        k = (lambda x, n, axis: torch.repeat_interleave(x, n, dim=axis))(k_cache[:, :, Sk - W:, :], rep, axis=1)
        v = (lambda x, n, axis: torch.repeat_interleave(x, n, dim=axis))(v_cache[:, :, Sk - W:, :], rep, axis=1)
        scores = torch.einsum("bhqd,bhkd->bhqk", q, k) * (Dh ** -0.5)
        p = _softmax(scores, axis=-1)
        o = torch.einsum("bhqk,bhkd->bhqd", p, v)
        return (lambda x, *d: x.permute(*d))(o, 0, 2, 1, 3).reshape(B, Sq, Hq * Dh) @ wo

    a = _A_ref(A_x, A_k_cache, A_v_cache, A_wq, A_wo)
    b = _B_ref(B_x, B_k_cache, B_v_cache, B_wq, B_wo)
    return torch.concatenate([a, b], axis=-1)
```

```cpp
#include <cuda_runtime.h>
#include <cuda_bf16.h>
#include <stdint.h>

namespace {

constexpr int B_      = 4;
constexpr int D_      = 640;
constexpr int H_      = 32;
constexpr int SK_     = 8192;
constexpr int DH_     = 128;
constexpr int W_      = 2048;
constexpr int HD_     = H_ * DH_;

constexpr int NCTA    = 128;
constexpr int NSW     = 8;
constexpr int THREADS = 320;
constexpr int UKEYS   = 16;
constexpr int UBYTES  = UKEYS * DH_ * 2;
constexpr int NST     = 3;
constexpr int KEYS_PER_WARP = W_ / 4;
constexpr int NIT     = KEYS_PER_WARP / UKEYS;

constexpr int SM_RING   = 0;
constexpr int SM_RED    = SM_RING + NSW * 2 * NST * UBYTES;
constexpr int SM_XS     = SM_RED + 8 * 2 * 128 * 4;
constexpr int SM_QS     = SM_XS + 2 * D_ * 4;
constexpr int SM_WO     = SM_QS + 2 * DH_ * 4;
constexpr int SM_WML    = SM_WO + NSW * DH_ * 4;
constexpr int SM_OS     = SM_WML + NSW * 2 * 4;
constexpr int SM_BAR    = SM_OS + 2 * DH_ * 4;
constexpr int SM_TOTAL  = SM_BAR + NSW * 2 * NST * 8;

__device__ float    g_part[NCTA * 2 * D_];
__device__ unsigned g_bar;

__device__ __forceinline__ uint32_t smem_u32(const void* p) {
    return (uint32_t)__cvta_generic_to_shared(p);
}
__device__ __forceinline__ void mbar_init(uint32_t bar, uint32_t cnt) {
    asm volatile("mbarrier.init.shared::cta.b64 [%0], %1;" :: "r"(bar), "r"(cnt) : "memory");
}
__device__ __forceinline__ void mbar_expect_tx(uint32_t bar, uint32_t bytes) {
    asm volatile("mbarrier.arrive.expect_tx.shared::cta.b64 _, [%0], %1;" :: "r"(bar), "r"(bytes) : "memory");
}
__device__ __forceinline__ bool mbar_try_wait(uint32_t bar, uint32_t parity) {
    uint32_t ok;
    asm volatile("{\n\t.reg .pred p;\n\t"
                 "mbarrier.try_wait.parity.shared::cta.b64 p, [%1], %2;\n\t"
                 "selp.u32 %0, 1, 0, p;\n\t}"
                 : "=r"(ok) : "r"(bar), "r"(parity) : "memory");
    return ok != 0;
}
__device__ __forceinline__ void mbar_wait(uint32_t bar, uint32_t parity) {
    for (int i = 0; i < (1 << 22); ++i)
        if (mbar_try_wait(bar, parity)) return;
    __trap();
}
__device__ __forceinline__ void bulk_g2s(uint32_t dst, const void* src, uint32_t bytes, uint32_t bar) {
    asm volatile("cp.async.bulk.shared::cluster.global.mbarrier::complete_tx::bytes [%0], [%1], %2, [%3];"
                 :: "r"(dst), "l"(src), "r"(bytes), "r"(bar) : "memory");
}
__device__ __forceinline__ uint4 lds128(uint32_t addr) {
    uint4 v;
    asm volatile("ld.shared.v4.u32 {%0,%1,%2,%3}, [%4];" : "=r"(v.x), "=r"(v.y), "=r"(v.z), "=r"(v.w) : "r"(addr) : "memory");
    return v;
}
__device__ __forceinline__ uint4 ldg128_nc(const void* p) {
    uint4 v;
    asm volatile("ld.global.nc.L1::no_allocate.v4.u32 {%0,%1,%2,%3}, [%4];" : "=r"(v.x), "=r"(v.y), "=r"(v.z), "=r"(v.w) : "l"(p));
    return v;
}
__device__ __forceinline__ float bf_lo(uint32_t x) { return __uint_as_float(x << 16); }
__device__ __forceinline__ float bf_hi(uint32_t x) { return __uint_as_float(x & 0xffff0000u); }
__device__ __forceinline__ float bf_round(float x) { return __bfloat162float(__float2bfloat16_rn(x)); }

__device__ __forceinline__ void unpack8(const uint4& v, float (&f)[8]) {
    f[0] = bf_lo(v.x); f[1] = bf_hi(v.x); f[2] = bf_lo(v.y); f[3] = bf_hi(v.y);
    f[4] = bf_lo(v.z); f[5] = bf_hi(v.z); f[6] = bf_lo(v.w); f[7] = bf_hi(v.w);
}

__device__ __forceinline__ void grid_barrier() {
    __syncthreads();
    if (threadIdx.x == 0) {
        __threadfence();
        unsigned old = atomicAdd(&g_bar, 1u);
        unsigned target = (old / NCTA + 1u) * NCTA;
        unsigned cur;
        int spins = 0;
        do {
            asm volatile("ld.acquire.gpu.global.u32 %0, [%1];" : "=r"(cur) : "l"(&g_bar) : "memory");
            if (++spins > (1 << 24)) __trap();
        } while ((int)(cur - target) < 0);
        __threadfence();
    }
    __syncthreads();
}

struct Params {
    const __nv_bfloat16* x[2];
    const __nv_bfloat16* k[2];
    const __nv_bfloat16* v[2];
    const __nv_bfloat16* wq[2];
    const __nv_bfloat16* wo[2];
    __nv_bfloat16* out;
};

__global__ void __launch_bounds__(THREADS, 1)
fused_decode_kernel(const Params P) {
    extern __shared__ __align__(128) unsigned char smem[];
    const uint32_t sbase = smem_u32(smem);
    const int tid  = threadIdx.x;
    const int warp = tid >> 5;
    const int lane = tid & 31;

    const int cta = blockIdx.x;
    const int p   = cta >> 6;
    const int h   = (cta >> 1) & 31;
    const int b0  = (cta & 1) * 2;

    float* s_red = reinterpret_cast<float*>(smem + SM_RED);
    float* s_xs  = reinterpret_cast<float*>(smem + SM_XS);
    float* s_qs  = reinterpret_cast<float*>(smem + SM_QS);
    float* s_wo  = reinterpret_cast<float*>(smem + SM_WO);
    float* s_wml = reinterpret_cast<float*>(smem + SM_WML);
    float* s_os  = reinterpret_cast<float*>(smem + SM_OS);

    const uint32_t kbuf = sbase + SM_RING + warp * (2 * NST * UBYTES);
    const uint32_t vbuf = kbuf + NST * UBYTES;
    const uint32_t kbar = sbase + SM_BAR + warp * (2 * NST * 8);
    const uint32_t vbar = kbar + NST * 8;
    const unsigned char* kg = nullptr;
    const unsigned char* vg = nullptr;
    if (warp < NSW) {
        const int pb = b0 + (warp >> 2);
        const size_t off = (((size_t)(pb * H_ + h) * SK_) + (SK_ - W_) + (size_t)(warp & 3) * KEYS_PER_WARP) * DH_;
        kg = reinterpret_cast<const unsigned char*>(P.k[p] + off);
        vg = reinterpret_cast<const unsigned char*>(P.v[p] + off);
        if (lane == 0) {
            #pragma unroll
            for (int s = 0; s < NST; ++s) { mbar_init(kbar + s * 8, 1); mbar_init(vbar + s * 8, 1); }
            asm volatile("fence.mbarrier_init.release.cluster;" ::: "memory");
            asm volatile("fence.proxy.async.shared::cta;" ::: "memory");
            #pragma unroll
            for (int s = 0; s < NST; ++s) {
                mbar_expect_tx(kbar + s * 8, UBYTES);
                bulk_g2s(kbuf + s * UBYTES, kg + (size_t)s * UBYTES, UBYTES, kbar + s * 8);
                mbar_expect_tx(vbar + s * 8, UBYTES);
                bulk_g2s(vbuf + s * UBYTES, vg + (size_t)s * UBYTES, UBYTES, vbar + s * 8);
            }
        }
        __syncwarp();
    }

    for (int i = tid; i < 2 * D_; i += THREADS)
        s_xs[i] = __bfloat162float(P.x[p][(b0 + i / D_) * D_ + (i % D_)]);
    __syncthreads();
    if (tid < 256) {
        const int c  = tid & 15;
        const int rg = tid >> 4;
        const __nv_bfloat16* wp = P.wq[p] + (size_t)rg * HD_ + h * DH_ + c * 8;
        float a0[8], a1[8];
        #pragma unroll
        for (int e = 0; e < 8; ++e) { a0[e] = 0.f; a1[e] = 0.f; }
        #pragma unroll 1
        for (int i0 = 0; i0 < 40; i0 += 10) {
            uint4 w[10];
            #pragma unroll
            for (int i = 0; i < 10; ++i) w[i] = ldg128_nc(wp + (size_t)(i0 + i) * 16 * HD_);
            #pragma unroll
            for (int i = 0; i < 10; ++i) {
                const int row = rg + (i0 + i) * 16;
                const float x0 = s_xs[row], x1 = s_xs[D_ + row];
                float f[8]; unpack8(w[i], f);
                #pragma unroll
                for (int e = 0; e < 8; ++e) { a0[e] = fmaf(x0, f[e], a0[e]); a1[e] = fmaf(x1, f[e], a1[e]); }
            }
        }
        #pragma unroll
        for (int e = 0; e < 8; ++e) {
            a0[e] += __shfl_xor_sync(0xffffffffu, a0[e], 16);
            a1[e] += __shfl_xor_sync(0xffffffffu, a1[e], 16);
        }
        if (lane < 16) {
            #pragma unroll
            for (int e = 0; e < 8; ++e) {
                s_red[(warp * 2 + 0) * 128 + c * 8 + e] = a0[e];
                s_red[(warp * 2 + 1) * 128 + c * 8 + e] = a1[e];
            }
        }
    }
    __syncthreads();
    if (tid < 256) {
        float s = 0.f;
        #pragma unroll
        for (int w = 0; w < 8; ++w) s += s_red[w * 256 + tid];
        s_qs[tid] = bf_round(s);
    }
    __syncthreads();

    if (warp < NSW) {
        const int hl = lane & 15;
        const int hf = lane >> 4;
        float q[8];
        #pragma unroll
        for (int e = 0; e < 8; ++e) q[e] = s_qs[(warp >> 2) * DH_ + hl * 8 + e];
        float acc[8];
        #pragma unroll
        for (int e = 0; e < 8; ++e) acc[e] = 0.f;
        float m = -INFINITY, l = 0.f;
        const float scale = 0.08838834764831845f;
        const float LOG2E = 1.4426950408889634f;

        int slot = 0; uint32_t ph = 0;
        #pragma unroll 1
        for (int it = 0; it < NIT; ++it) {
            mbar_wait(kbar + slot * 8, ph);
            float v[8];
            {
                const uint32_t ka = kbuf + slot * UBYTES + lane * 16;
                #pragma unroll
                for (int s = 0; s < 8; ++s) {
                    uint4 x = lds128(ka + s * 512);
                    float f[8]; unpack8(x, f);
                    float d = f[0] * q[0];
                    #pragma unroll
                    for (int e = 1; e < 8; ++e) d = fmaf(f[e], q[e], d);
                    v[s] = d;
                }
            }
            __syncwarp();
            if (lane == 0 && it + NST < NIT) {
                mbar_expect_tx(kbar + slot * 8, UBYTES);
                bulk_g2s(kbuf + slot * UBYTES, kg + (size_t)(it + NST) * UBYTES, UBYTES, kbar + slot * 8);
            }
            float r4[4], r2[2], r1;
            {
                const bool up = lane & 8;
                #pragma unroll
                for (int j = 0; j < 4; ++j) {
                    float snd = up ? v[j] : v[j + 4];
                    float kep = up ? v[j + 4] : v[j];
                    r4[j] = kep + __shfl_xor_sync(0xffffffffu, snd, 8);
                }
            }
            {
                const bool up = lane & 4;
                #pragma unroll
                for (int j = 0; j < 2; ++j) {
                    float snd = up ? r4[j] : r4[j + 2];
                    float kep = up ? r4[j + 2] : r4[j];
                    r2[j] = kep + __shfl_xor_sync(0xffffffffu, snd, 4);
                }
            }
            {
                const bool up = lane & 2;
                float snd = up ? r2[0] : r2[1];
                float kep = up ? r2[1] : r2[0];
                r1 = kep + __shfl_xor_sync(0xffffffffu, snd, 2);
            }
            r1 += __shfl_xor_sync(0xffffffffu, r1, 1);
            float sc = bf_round(bf_round(r1) * scale);
            float mx = sc;
            #pragma unroll
            for (int o = 16; o >= 2; o >>= 1) mx = fmaxf(mx, __shfl_xor_sync(0xffffffffu, mx, o));
            if (mx > m) {
                const float corr = exp2f((m - mx) * LOG2E);
                l *= corr;
                #pragma unroll
                for (int e = 0; e < 8; ++e) acc[e] *= corr;
                m = mx;
            }
            const float pv = exp2f((sc - m) * LOG2E);
            l += pv;

            mbar_wait(vbar + slot * 8, ph);
            {
                const uint32_t va = vbuf + slot * UBYTES + lane * 16;
                #pragma unroll
                for (int s = 0; s < 8; ++s) {
                    const float pk = __shfl_sync(0xffffffffu, pv, (lane & 16) + 2 * s);
                    uint4 x = lds128(va + s * 512);
                    float f[8]; unpack8(x, f);
                    #pragma unroll
                    for (int e = 0; e < 8; ++e) acc[e] = fmaf(pk, f[e], acc[e]);
                }
            }
            __syncwarp();
            if (lane == 0 && it + NST < NIT) {
                mbar_expect_tx(vbar + slot * 8, UBYTES);
                bulk_g2s(vbuf + slot * UBYTES, vg + (size_t)(it + NST) * UBYTES, UBYTES, vbar + slot * 8);
            }
            if (++slot == NST) { slot = 0; ph ^= 1; }
        }
        #pragma unroll
        for (int e = 0; e < 8; ++e) acc[e] += __shfl_xor_sync(0xffffffffu, acc[e], 16);
        #pragma unroll
        for (int o = 16; o >= 1; o >>= 1) l += __shfl_xor_sync(0xffffffffu, l, o);
        l *= 0.5f;
        if (hf == 0) {
            #pragma unroll
            for (int e = 0; e < 8; ++e) s_wo[warp * DH_ + hl * 8 + e] = acc[e];
        }
        if (lane == 0) { s_wml[warp * 2] = m; s_wml[warp * 2 + 1] = l; }
    }
    __syncthreads();

    if (tid < 256) {
        const int pr = tid >> 7, d = tid & 127;
        const float LOG2E = 1.4426950408889634f;
        float M = -INFINITY;
        #pragma unroll
        for (int w = 0; w < 4; ++w) M = fmaxf(M, s_wml[(pr * 4 + w) * 2]);
        float L = 0.f, o = 0.f;
        #pragma unroll
        for (int w = 0; w < 4; ++w) {
            const float c = exp2f((s_wml[(pr * 4 + w) * 2] - M) * LOG2E);
            L = fmaf(s_wml[(pr * 4 + w) * 2 + 1], c, L);
            o = fmaf(s_wo[(pr * 4 + w) * DH_ + d], c, o);
        }
        s_os[tid] = bf_round(o / L);
    }
    __syncthreads();

    {
        const int c  = tid % 80;
        const int rg = tid / 80;
        const __nv_bfloat16* wp = P.wo[p] + (size_t)(h * DH_ + rg * 32) * D_ + c * 8;
        float a0[8], a1[8];
        #pragma unroll
        for (int e = 0; e < 8; ++e) { a0[e] = 0.f; a1[e] = 0.f; }
        #pragma unroll 1
        for (int i0 = 0; i0 < 32; i0 += 16) {
            uint4 w[16];
            #pragma unroll
            for (int i = 0; i < 16; ++i) w[i] = ldg128_nc(wp + (size_t)(i0 + i) * D_);
            #pragma unroll
            for (int i = 0; i < 16; ++i) {
                const int row = rg * 32 + i0 + i;
                const float o0 = s_os[row], o1 = s_os[DH_ + row];
                float f[8]; unpack8(w[i], f);
                #pragma unroll
                for (int e = 0; e < 8; ++e) { a0[e] = fmaf(o0, f[e], a0[e]); a1[e] = fmaf(o1, f[e], a1[e]); }
            }
        }
        float* s_pr = reinterpret_cast<float*>(smem + SM_RING);
        #pragma unroll
        for (int e = 0; e < 8; ++e) {
            s_pr[(rg * 2 + 0) * D_ + c * 8 + e] = a0[e];
            s_pr[(rg * 2 + 1) * D_ + c * 8 + e] = a1[e];
        }
        __syncthreads();
        for (int i = tid; i < 2 * D_; i += THREADS) {
            float s = s_pr[i] + s_pr[2 * D_ + i] + s_pr[4 * D_ + i] + s_pr[6 * D_ + i];
            g_part[cta * 2 * D_ + i] = s;
        }
    }

    grid_barrier();

    if (tid < 40) {
        const int row = cta >> 4;
        const int pp  = row >> 2, bb = row & 3;
        const int n   = (cta & 15) * 40 + tid;
        const float* src = g_part + ((size_t)(pp * 64 + (bb >> 1)) * 2 + (bb & 1)) * D_ + n;
        float vals[32];
        #pragma unroll
        for (int hh = 0; hh < 32; ++hh) vals[hh] = __ldcg(src + (size_t)hh * 4 * D_);
        float s = 0.f;
        #pragma unroll
        for (int hh = 0; hh < 32; ++hh) s += vals[hh];
        P.out[bb * (2 * D_) + pp * D_ + n] = __float2bfloat16_rn(s);
    }
}

}

extern "C" void kernel_launch(void* const* d_in, const int* in_sizes, int n_in,
                              void* d_out, int out_size) {
    (void)in_sizes; (void)n_in; (void)out_size;
    static bool attr_set = false;
    if (!attr_set) {
        cudaFuncSetAttribute(fused_decode_kernel, cudaFuncAttributeMaxDynamicSharedMemorySize, SM_TOTAL);
        attr_set = true;
    }
    Params P;
    for (int p = 0; p < 2; ++p) {
        P.x[p]  = (const __nv_bfloat16*)d_in[p * 5 + 0];
        P.k[p]  = (const __nv_bfloat16*)d_in[p * 5 + 1];
        P.v[p]  = (const __nv_bfloat16*)d_in[p * 5 + 2];
        P.wq[p] = (const __nv_bfloat16*)d_in[p * 5 + 3];
        P.wo[p] = (const __nv_bfloat16*)d_in[p * 5 + 4];
    }
    P.out = (__nv_bfloat16*)d_out;
    fused_decode_kernel<<<NCTA, THREADS, SM_TOTAL>>>(P);
}
```

```cpp
#include <cuda_runtime.h>
#include <cuda_bf16.h>
#include <stdint.h>

namespace {

constexpr int D_      = 640;
constexpr int H_      = 32;
constexpr int SK_     = 8192;
constexpr int DH_     = 128;
constexpr int W_      = 2048;
constexpr int HD_     = H_ * DH_;

constexpr int NCTA    = 128;
constexpr int NSW     = 8;
constexpr int THREADS = 320;
constexpr int UKEYS   = 16;
constexpr int UBYTES  = UKEYS * DH_ * 2;
constexpr int NST     = 2;
constexpr int KEYS_PER_WARP = W_ / 4;
constexpr int NIT     = KEYS_PER_WARP / UKEYS;
#define KV_GATE -1
constexpr int WO_STRIDE = D_ * 2 + 16;

constexpr int SM_RING   = 0;
constexpr int SM_WOS    = SM_RING + NSW * 2 * NST * UBYTES;
constexpr int SM_RED    = SM_WOS + 64 * WO_STRIDE;
constexpr int SM_QS     = SM_RED + 10 * 4 * 64 * 4;
constexpr int SM_WML    = SM_QS + 2 * DH_ * 4;
constexpr int SM_OA     = SM_WML + NSW * 2 * 4;
constexpr int SM_BAR    = SM_OA + 4 * 64 * 2;
constexpr int SM_TOTAL  = SM_BAR + (NSW * 2 * NST + 1) * 8;
static_assert(SM_TOTAL <= 232448, "smem");

__device__ float    g_part[NCTA * 4 * D_];
__device__ unsigned g_bar;

#define STAMP(cond, slot) do {} while (0)

__device__ __forceinline__ uint32_t smem_u32(const void* p) {
    return (uint32_t)__cvta_generic_to_shared(p);
}
__device__ __forceinline__ void mbar_init(uint32_t bar, uint32_t cnt) {
    asm volatile("mbarrier.init.shared::cta.b64 [%0], %1;" :: "r"(bar), "r"(cnt) : "memory");
}
__device__ __forceinline__ void mbar_expect_tx(uint32_t bar, uint32_t bytes) {
    asm volatile("mbarrier.arrive.expect_tx.shared::cta.b64 _, [%0], %1;" :: "r"(bar), "r"(bytes) : "memory");
}
__device__ __forceinline__ bool mbar_try_wait(uint32_t bar, uint32_t parity) {
    uint32_t ok;
    asm volatile("{\n\t.reg .pred p;\n\t"
                 "mbarrier.try_wait.parity.shared::cta.b64 p, [%1], %2;\n\t"
                 "selp.u32 %0, 1, 0, p;\n\t}"
                 : "=r"(ok) : "r"(bar), "r"(parity) : "memory");
    return ok != 0;
}
__device__ __forceinline__ void mbar_wait(uint32_t bar, uint32_t parity) {
    for (int i = 0; i < (1 << 22); ++i)
        if (mbar_try_wait(bar, parity)) return;
    __trap();
}
__device__ __forceinline__ void bulk_g2s(uint32_t dst, const void* src, uint32_t bytes, uint32_t bar) {
    asm volatile("cp.async.bulk.shared::cluster.global.mbarrier::complete_tx::bytes [%0], [%1], %2, [%3];"
                 :: "r"(dst), "l"(src), "r"(bytes), "r"(bar) : "memory");
}
__device__ __forceinline__ uint4 lds128(uint32_t addr) {
    uint4 v;
    asm volatile("ld.shared.v4.u32 {%0,%1,%2,%3}, [%4];" : "=r"(v.x), "=r"(v.y), "=r"(v.z), "=r"(v.w) : "r"(addr) : "memory");
    return v;
}
__device__ __forceinline__ uint4 ldg128_nc(const void* p) {
    uint4 v;
    asm volatile("ld.global.nc.L1::no_allocate.v4.u32 {%0,%1,%2,%3}, [%4];" : "=r"(v.x), "=r"(v.y), "=r"(v.z), "=r"(v.w) : "l"(p));
    return v;
}
__device__ __forceinline__ uint32_t mapa(uint32_t addr, uint32_t rank) {
    uint32_t r; asm volatile("mapa.shared::cluster.u32 %0, %1, %2;" : "=r"(r) : "r"(addr), "r"(rank)); return r;
}
__device__ __forceinline__ void st_cluster_f32(uint32_t addr, float v) {
    asm volatile("st.shared::cluster.f32 [%0], %1;" :: "r"(addr), "f"(v) : "memory");
}
__device__ __forceinline__ void st_cluster_u16(uint32_t addr, unsigned short v) {
    asm volatile("st.shared::cluster.u16 [%0], %1;" :: "r"(addr), "h"(v) : "memory");
}
__device__ __forceinline__ void cluster_arrive() { asm volatile("barrier.cluster.arrive.release.aligned;" ::: "memory"); }
__device__ __forceinline__ void cluster_wait()   { asm volatile("barrier.cluster.wait.acquire.aligned;" ::: "memory"); }

__device__ __forceinline__ float bf_lo(uint32_t x) { return __uint_as_float(x << 16); }
__device__ __forceinline__ float bf_hi(uint32_t x) { return __uint_as_float(x & 0xffff0000u); }
__device__ __forceinline__ float bf_round(float x) { return __bfloat162float(__float2bfloat16_rn(x)); }

__device__ __forceinline__ void unpack8(const uint4& v, float (&f)[8]) {
    f[0] = bf_lo(v.x); f[1] = bf_hi(v.x); f[2] = bf_lo(v.y); f[3] = bf_hi(v.y);
    f[4] = bf_lo(v.z); f[5] = bf_hi(v.z); f[6] = bf_lo(v.w); f[7] = bf_hi(v.w);
}

__device__ __forceinline__ void mma_bf16(float (&c)[4], uint32_t a0, uint32_t a1, uint32_t a2, uint32_t a3,
                                         uint32_t b0, uint32_t b1) {
    asm volatile("mma.sync.aligned.m16n8k16.row.col.f32.bf16.bf16.f32 {%0,%1,%2,%3}, {%4,%5,%6,%7}, {%8,%9}, {%0,%1,%2,%3};"
                 : "+f"(c[0]), "+f"(c[1]), "+f"(c[2]), "+f"(c[3])
                 : "r"(a0), "r"(a1), "r"(a2), "r"(a3), "r"(b0), "r"(b1));
}

__device__ __forceinline__ void grid_barrier() {
    __syncthreads();
    if (threadIdx.x == 0) {
        __threadfence();
        unsigned old = atomicAdd(&g_bar, 1u);
        unsigned target = (old / NCTA + 1u) * NCTA;
        unsigned cur;
        int spins = 0;
        do {
            asm volatile("ld.acquire.gpu.global.u32 %0, [%1];" : "=r"(cur) : "l"(&g_bar) : "memory");
            if (++spins > (1 << 24)) __trap();
        } while ((int)(cur - target) < 0);
        __threadfence();
    }
    __syncthreads();
}

struct Params {
    const __nv_bfloat16* x[2];
    const __nv_bfloat16* k[2];
    const __nv_bfloat16* v[2];
    const __nv_bfloat16* wq[2];
    const __nv_bfloat16* wo[2];
    __nv_bfloat16* out;
};

__global__ void __cluster_dims__(2, 1, 1) __launch_bounds__(THREADS, 1)
fused_decode_kernel(const Params P) {
    extern __shared__ __align__(128) unsigned char smem[];
    const uint32_t sbase = smem_u32(smem);
    const int tid  = threadIdx.x;
    const int warp = tid >> 5;
    const int lane = tid & 31;

    const int cta = blockIdx.x;
    STAMP(tid == 0, 0);
    const int p   = cta >> 6;
    const int h   = (cta >> 1) & 31;
    const int r   = cta & 1;
    const int b0  = r * 2;

    const __nv_bfloat16* g_x  = p ? P.x[1]  : P.x[0];
    const __nv_bfloat16* g_k  = p ? P.k[1]  : P.k[0];
    const __nv_bfloat16* g_v  = p ? P.v[1]  : P.v[0];
    const __nv_bfloat16* g_wq = p ? P.wq[1] : P.wq[0];
    const __nv_bfloat16* g_wo = p ? P.wo[1] : P.wo[0];

    float* s_red = reinterpret_cast<float*>(smem + SM_RED);
    float* s_qs  = reinterpret_cast<float*>(smem + SM_QS);
    float* s_wo  = reinterpret_cast<float*>(smem + SM_RED);
    float* s_wml = reinterpret_cast<float*>(smem + SM_WML);

    cluster_arrive();

    const int g = lane >> 2, t = lane & 3;
    uint4 wreg[16];
    uint32_t xa[8];
    {
        const __nv_bfloat16* wp = g_wq + (size_t)(warp * 64 + 2 * t) * HD_ + h * DH_ + r * 64 + g * 8;
        #pragma unroll
        for (int j = 0; j < 4; ++j) {
            wreg[j * 4 + 0] = ldg128_nc(wp + (size_t)(j * 16 + 0) * HD_);
            wreg[j * 4 + 1] = ldg128_nc(wp + (size_t)(j * 16 + 1) * HD_);
            wreg[j * 4 + 2] = ldg128_nc(wp + (size_t)(j * 16 + 8) * HD_);
            wreg[j * 4 + 3] = ldg128_nc(wp + (size_t)(j * 16 + 9) * HD_);
        }
        const uint32_t* xp = reinterpret_cast<const uint32_t*>(g_x + (g & 3) * D_ + warp * 64 + 2 * t);
        #pragma unroll
        for (int j = 0; j < 4; ++j) {
            xa[j * 2 + 0] = (g < 4) ? __ldg(xp + j * 8)     : 0u;
            xa[j * 2 + 1] = (g < 4) ? __ldg(xp + j * 8 + 4) : 0u;
        }
    }

    const uint32_t kbuf = sbase + SM_RING + warp * (2 * NST * UBYTES);
    const uint32_t vbuf = kbuf + NST * UBYTES;
    const uint32_t kbar = sbase + SM_BAR + warp * (2 * NST * 8);
    const uint32_t vbar = kbar + NST * 8;
    const uint32_t wobar = sbase + SM_BAR + NSW * 2 * NST * 8;
    const unsigned char* kg = nullptr;
    const unsigned char* vg = nullptr;
    if (warp < NSW) {
        const int pb = b0 + (warp >> 2);
        const size_t off = (((size_t)(pb * H_ + h) * SK_) + (SK_ - W_) + (size_t)(warp & 3) * KEYS_PER_WARP) * DH_;
        kg = reinterpret_cast<const unsigned char*>(g_k + off);
        vg = reinterpret_cast<const unsigned char*>(g_v + off);
        if (lane == 0) {
            #pragma unroll
            for (int s = 0; s < NST; ++s) { mbar_init(kbar + s * 8, 1); mbar_init(vbar + s * 8, 1); }
            asm volatile("fence.mbarrier_init.release.cluster;" ::: "memory");
            asm volatile("fence.proxy.async.shared::cta;" ::: "memory");
            #pragma unroll
            for (int s = 0; s < NST; ++s) {
                mbar_expect_tx(kbar + s * 8, UBYTES);
                bulk_g2s(kbuf + s * UBYTES, kg + (size_t)s * UBYTES, UBYTES, kbar + s * 8);
                mbar_expect_tx(vbar + s * 8, UBYTES);
                bulk_g2s(vbuf + s * UBYTES, vg + (size_t)s * UBYTES, UBYTES, vbar + s * 8);
            }
        }
        __syncwarp();
    } else if (warp == NSW && lane == 0) {
        mbar_init(wobar, 1);
        asm volatile("fence.mbarrier_init.release.cluster;" ::: "memory");
        asm volatile("fence.proxy.async.shared::cta;" ::: "memory");
    }

    {
        float c[8][4];
        #pragma unroll
        for (int e = 0; e < 8; ++e) { c[e][0] = c[e][1] = c[e][2] = c[e][3] = 0.f; }
        #pragma unroll
        for (int j = 0; j < 4; ++j) {
            const uint4 x0 = wreg[j * 4 + 0], x1 = wreg[j * 4 + 1], x2 = wreg[j * 4 + 2], x3 = wreg[j * 4 + 3];
            const uint32_t w0[4] = {x0.x, x0.y, x0.z, x0.w};
            const uint32_t w1[4] = {x1.x, x1.y, x1.z, x1.w};
            const uint32_t w2[4] = {x2.x, x2.y, x2.z, x2.w};
            const uint32_t w3[4] = {x3.x, x3.y, x3.z, x3.w};
            #pragma unroll
            for (int e = 0; e < 8; ++e) {
                const uint32_t sel = (e & 1) ? 0x7632u : 0x5410u;
                const uint32_t b0r = __byte_perm(w0[e >> 1], w1[e >> 1], sel);
                const uint32_t b1r = __byte_perm(w2[e >> 1], w3[e >> 1], sel);
                mma_bf16(c[e], xa[j * 2], 0u, xa[j * 2 + 1], 0u, b0r, b1r);
            }
        }
        if (g < 4) {
            float* dst = s_red + (warp * 4 + g) * 64 + t * 16;
            *reinterpret_cast<float4*>(dst)      = make_float4(c[0][0], c[1][0], c[2][0], c[3][0]);
            *reinterpret_cast<float4*>(dst + 4)  = make_float4(c[4][0], c[5][0], c[6][0], c[7][0]);
            *reinterpret_cast<float4*>(dst + 8)  = make_float4(c[0][1], c[1][1], c[2][1], c[3][1]);
            *reinterpret_cast<float4*>(dst + 12) = make_float4(c[4][1], c[5][1], c[6][1], c[7][1]);
        }
    }
    __syncthreads();
    STAMP(tid == 0, 16 + 2);
    cluster_wait();
    STAMP(tid == 0, 16 + 3);
    if (tid < 256) {
        float s = 0.f;
        #pragma unroll
        for (int w = 0; w < 10; ++w) s += s_red[w * 256 + tid];
        s = bf_round(s);
        const int b = tid >> 6, col = tid & 63;
        const uint32_t dst = sbase + SM_QS + ((b & 1) * DH_ + r * 64 + col) * 4;
        st_cluster_f32(mapa(dst, (uint32_t)(b >> 1)), s);
    }
    cluster_arrive();
    cluster_wait();

    if (warp == NSW) {
        if (lane == 0) mbar_expect_tx(wobar, 64 * D_ * 2);
        __syncwarp();
        const unsigned char* src = reinterpret_cast<const unsigned char*>(g_wo + (size_t)(h * DH_ + r * 64) * D_);
        #pragma unroll
        for (int i = 0; i < 2; ++i) {
            const int row = lane + i * 32;
            bulk_g2s(sbase + SM_WOS + row * WO_STRIDE, src + (size_t)row * (D_ * 2), D_ * 2, wobar);
        }
    }

    STAMP(tid == 0, 1);
    int pass = (warp >= NSW) ? 0 : 1;
    #pragma unroll 1
    for (; pass < 2; ++pass) {
    asm volatile("" : "+r"(pass));
    const bool real = pass != 0;
    if (real) {
    if (warp < NSW) {
        const int hl = lane & 15;
        const int hf = lane >> 4;
        float q[8];
        #pragma unroll
        for (int e = 0; e < 8; ++e) q[e] = s_qs[(warp >> 2) * DH_ + hl * 8 + e];
        float acc[8];
        #pragma unroll
        for (int e = 0; e < 8; ++e) acc[e] = 0.f;
        float m = -INFINITY, l = 0.f;
        const float scale = 0.08838834764831845f;
        const float LOG2E = 1.4426950408889634f;

        int slot = 0; uint32_t ph = 0;
        #pragma unroll 1
        for (int it = 0; it < NIT; ++it) {
            mbar_wait(kbar + slot * 8, ph);
            float v[8];
            {
                const uint32_t ka = kbuf + slot * UBYTES + lane * 16;
                #pragma unroll
                for (int s = 0; s < 8; ++s) {
                    uint4 x = lds128(ka + s * 512);
                    float f[8]; unpack8(x, f);
                    float d = f[0] * q[0];
                    #pragma unroll
                    for (int e = 1; e < 8; ++e) d = fmaf(f[e], q[e], d);
                    v[s] = d;
                }
            }
            __syncwarp();
            if (lane == 0 && it + NST < NIT) {
                mbar_expect_tx(kbar + slot * 8, UBYTES);
                bulk_g2s(kbuf + slot * UBYTES, kg + (size_t)(it + NST) * UBYTES, UBYTES, kbar + slot * 8);
            }
            float r4[4], r2[2], r1;
            {
                const bool up = lane & 8;
                #pragma unroll
                for (int j = 0; j < 4; ++j) {
                    float snd = up ? v[j] : v[j + 4];
                    float kep = up ? v[j + 4] : v[j];
                    r4[j] = kep + __shfl_xor_sync(0xffffffffu, snd, 8);
                }
            }
            {
                const bool up = lane & 4;
                #pragma unroll
                for (int j = 0; j < 2; ++j) {
                    float snd = up ? r4[j] : r4[j + 2];
                    float kep = up ? r4[j + 2] : r4[j];
                    r2[j] = kep + __shfl_xor_sync(0xffffffffu, snd, 4);
                }
            }
            {
                const bool up = lane & 2;
                float snd = up ? r2[0] : r2[1];
                float kep = up ? r2[1] : r2[0];
                r1 = kep + __shfl_xor_sync(0xffffffffu, snd, 2);
            }
            r1 += __shfl_xor_sync(0xffffffffu, r1, 1);
            float sc = bf_round(bf_round(r1) * scale);
            float mx = sc;
            #pragma unroll
            for (int o = 16; o >= 2; o >>= 1) mx = fmaxf(mx, __shfl_xor_sync(0xffffffffu, mx, o));
            if (mx > m) {
                const float corr = exp2f((m - mx) * LOG2E);
                l *= corr;
                #pragma unroll
                for (int e = 0; e < 8; ++e) acc[e] *= corr;
                m = mx;
            }
            const float pv = exp2f((sc - m) * LOG2E);
            l += pv;

            mbar_wait(vbar + slot * 8, ph);
            {
                const uint32_t va = vbuf + slot * UBYTES + lane * 16;
                #pragma unroll
                for (int s = 0; s < 8; ++s) {
                    const float pk = __shfl_sync(0xffffffffu, pv, (lane & 16) + 2 * s);
                    uint4 x = lds128(va + s * 512);
                    float f[8]; unpack8(x, f);
                    #pragma unroll
                    for (int e = 0; e < 8; ++e) acc[e] = fmaf(pk, f[e], acc[e]);
                }
            }
            __syncwarp();
            if (lane == 0 && it + NST < NIT) {
                mbar_expect_tx(vbar + slot * 8, UBYTES);
                bulk_g2s(vbuf + slot * UBYTES, vg + (size_t)(it + NST) * UBYTES, UBYTES, vbar + slot * 8);
            }
            if (++slot == NST) { slot = 0; ph ^= 1; }
        }
        STAMP(lane == 0, 8 + warp);
        #pragma unroll
        for (int e = 0; e < 8; ++e) acc[e] += __shfl_xor_sync(0xffffffffu, acc[e], 16);
        #pragma unroll
        for (int o = 16; o >= 1; o >>= 1) l += __shfl_xor_sync(0xffffffffu, l, o);
        l *= 0.5f;
        if (hf == 0) {
            *reinterpret_cast<float4*>(&s_wo[warp * DH_ + hl * 8])     = make_float4(acc[0], acc[1], acc[2], acc[3]);
            *reinterpret_cast<float4*>(&s_wo[warp * DH_ + hl * 8 + 4]) = make_float4(acc[4], acc[5], acc[6], acc[7]);
        }
        if (lane == 0) { s_wml[warp * 2] = m; s_wml[warp * 2 + 1] = l; }
    }
    __syncthreads();
    }
    STAMP(tid == 0, 2);

    if (tid < 256 || !real) {
        const int pr = (tid >> 7) & 1, d = tid & 127;
        const float LOG2E = 1.4426950408889634f;
        float M = -INFINITY;
        #pragma unroll
        for (int w = 0; w < 4; ++w) M = fmaxf(M, s_wml[(pr * 4 + w) * 2]);
        float L = 0.f, o = 0.f;
        #pragma unroll
        for (int w = 0; w < 4; ++w) {
            const float c = exp2f((s_wml[(pr * 4 + w) * 2] - M) * LOG2E);
            L = fmaf(s_wml[(pr * 4 + w) * 2 + 1], c, L);
            o = fmaf(s_wo[(pr * 4 + w) * DH_ + d], c, o);
        }
        const __nv_bfloat16 ob = __float2bfloat16_rn(o / L);
        const uint32_t dst = sbase + SM_OA + ((b0 + pr) * 64 + (d & 63)) * 2;
        if (real) st_cluster_u16(mapa(dst, (uint32_t)(d >> 6)), __bfloat16_as_ushort(ob));
    }
    STAMP(tid == 0, 6);
    if (real) {
        cluster_arrive();
        cluster_wait();
    }
    STAMP(tid == 0, 7);

    {
        if (real) mbar_wait(wobar, 0);
        float c[8][4];
        #pragma unroll
        for (int e = 0; e < 8; ++e) { c[e][0] = c[e][1] = c[e][2] = c[e][3] = 0.f; }
        #pragma unroll
        for (int ks = 0; ks < 4; ++ks) {
            uint32_t a0 = 0, a2 = 0;
            if (g < 4) {
                a0 = *reinterpret_cast<const uint32_t*>(smem + SM_OA + (g * 64 + ks * 16 + 2 * t) * 2);
                a2 = *reinterpret_cast<const uint32_t*>(smem + SM_OA + (g * 64 + ks * 16 + 2 * t + 8) * 2);
            }
            const uint32_t wa = sbase + SM_WOS + (ks * 16 + 2 * t) * WO_STRIDE + (warp * 64 + g * 8) * 2;
            const uint4 x0 = lds128(wa);
            const uint4 x1 = lds128(wa + WO_STRIDE);
            const uint4 x2 = lds128(wa + 8 * WO_STRIDE);
            const uint4 x3 = lds128(wa + 9 * WO_STRIDE);
            const uint32_t w0[4] = {x0.x, x0.y, x0.z, x0.w};
            const uint32_t w1[4] = {x1.x, x1.y, x1.z, x1.w};
            const uint32_t w2[4] = {x2.x, x2.y, x2.z, x2.w};
            const uint32_t w3[4] = {x3.x, x3.y, x3.z, x3.w};
            #pragma unroll
            for (int e = 0; e < 8; ++e) {
                const uint32_t sel = (e & 1) ? 0x7632u : 0x5410u;
                const uint32_t b0r = __byte_perm(w0[e >> 1], w1[e >> 1], sel);
                const uint32_t b1r = __byte_perm(w2[e >> 1], w3[e >> 1], sel);
                mma_bf16(c[e], a0, 0u, a2, 0u, b0r, b1r);
            }
        }
        if (g < 4 && real) {
            float* dst = g_part + ((size_t)cta * 4 + g) * D_ + warp * 64 + t * 16;
            *reinterpret_cast<float4*>(dst)      = make_float4(c[0][0], c[1][0], c[2][0], c[3][0]);
            *reinterpret_cast<float4*>(dst + 4)  = make_float4(c[4][0], c[5][0], c[6][0], c[7][0]);
            *reinterpret_cast<float4*>(dst + 8)  = make_float4(c[0][1], c[1][1], c[2][1], c[3][1]);
            *reinterpret_cast<float4*>(dst + 12) = make_float4(c[4][1], c[5][1], c[6][1], c[7][1]);
        }
    }

    STAMP(tid == 0, 3);
    if (real) grid_barrier();
    STAMP(tid == 0, 4);

    {
        const int row = cta >> 4;
        const int pp  = row >> 2, bb = row & 3;
        const int j   = tid % 40, grp = tid / 40;
        const int n   = (cta & 15) * 40 + j;
        const float* src = g_part + ((size_t)(pp * 64 + grp * 8) * 4 + bb) * D_ + n;
        float vals[8];
        #pragma unroll
        for (int i = 0; i < 8; ++i) vals[i] = __ldcg(src + (size_t)i * 4 * D_);
        float s = 0.f;
        #pragma unroll
        for (int i = 0; i < 8; ++i) s += vals[i];
        if (real) {
            s_red[grp * 40 + j] = s;
            __syncthreads();
        }
        if (tid < 40 || !real) {
            float tot = 0.f;
            #pragma unroll
            for (int i = 0; i < 8; ++i) tot += s_red[i * 40 + j];
            if (real) P.out[bb * (2 * D_) + pp * D_ + n] = __float2bfloat16_rn(tot);
        }
    }
    }
    STAMP(tid == 0, 5);
}

}

extern "C" void kernel_launch(void* const* d_in, const int* in_sizes, int n_in,
                              void* d_out, int out_size) {
    (void)in_sizes; (void)n_in; (void)out_size;
    static bool attr_set = false;
    if (!attr_set) {
        cudaFuncSetAttribute(fused_decode_kernel, cudaFuncAttributeMaxDynamicSharedMemorySize, SM_TOTAL);
        attr_set = true;
    }
    Params P;
    for (int p = 0; p < 2; ++p) {
        P.x[p]  = (const __nv_bfloat16*)d_in[p * 5 + 0];
        P.k[p]  = (const __nv_bfloat16*)d_in[p * 5 + 1];
        P.v[p]  = (const __nv_bfloat16*)d_in[p * 5 + 2];
        P.wq[p] = (const __nv_bfloat16*)d_in[p * 5 + 3];
        P.wo[p] = (const __nv_bfloat16*)d_in[p * 5 + 4];
    }
    P.out = (__nv_bfloat16*)d_out;
    fused_decode_kernel<<<NCTA, THREADS, SM_TOTAL>>>(P);
}
```

```cpp
#include <cuda_runtime.h>
#include <cuda_bf16.h>
#include <stdint.h>

namespace {

constexpr int D_      = 640;
constexpr int H_      = 32;
constexpr int SK_     = 8192;
constexpr int DH_     = 128;
constexpr int W_      = 2048;
constexpr int HD_     = H_ * DH_;

constexpr int NCTA    = 128;
constexpr int NSW     = 8;
constexpr int THREADS = 320;
constexpr int UKEYS   = 16;
constexpr int UBYTES  = UKEYS * DH_ * 2;
constexpr int NST     = 2;
constexpr uint32_t UPP = W_ / UKEYS;
constexpr uint32_t NUNITS = 4 * UPP;
constexpr int WO_STRIDE = D_ * 2 + 16;

constexpr int SM_RING   = 0;
constexpr int SM_WOS    = SM_RING + NSW * 2 * NST * UBYTES;
constexpr int SM_ST     = SM_WOS + 64 * WO_STRIDE;
constexpr int SM_ML     = SM_ST + 16 * 4 * 64 * 4;
constexpr int SM_QS     = SM_ML + 16 * 4 * 2 * 4;
constexpr int SM_BAR    = SM_QS + 4 * DH_ * 2;
constexpr int SM_CNT    = SM_BAR + (NSW * 2 * NST + 3) * 8;
constexpr int SM_TOTAL  = SM_CNT + 8;
static_assert(SM_TOTAL <= 232448, "smem");

__device__ unsigned long long g_part[NCTA * 4 * D_];
__device__ unsigned           g_epoch[NCTA];
__device__ unsigned           g_cnt;

#define STAMP(cond, slot) do {} while (0)

__device__ __forceinline__ uint32_t smem_u32(const void* p) {
    return (uint32_t)__cvta_generic_to_shared(p);
}
__device__ __forceinline__ void mbar_init(uint32_t bar, uint32_t cnt) {
    asm volatile("mbarrier.init.shared::cta.b64 [%0], %1;" :: "r"(bar), "r"(cnt) : "memory");
}
__device__ __forceinline__ void mbar_expect_tx(uint32_t bar, uint32_t bytes) {
    asm volatile("mbarrier.arrive.expect_tx.shared::cta.b64 _, [%0], %1;" :: "r"(bar), "r"(bytes) : "memory");
}
__device__ __forceinline__ bool mbar_try_wait(uint32_t bar, uint32_t parity) {
    uint32_t ok;
    asm volatile("{\n\t.reg .pred p;\n\t"
                 "mbarrier.try_wait.parity.shared::cta.b64 p, [%1], %2;\n\t"
                 "selp.u32 %0, 1, 0, p;\n\t}"
                 : "=r"(ok) : "r"(bar), "r"(parity) : "memory");
    return ok != 0;
}
__device__ __forceinline__ void mbar_wait(uint32_t bar, uint32_t parity) {
    #pragma unroll 1
    for (int i = 0; i < (1 << 22); ++i)
        if (mbar_try_wait(bar, parity)) return;
    __trap();
}
__device__ __forceinline__ void bulk_g2s(uint32_t dst, const void* src, uint32_t bytes, uint32_t bar) {
    asm volatile("cp.async.bulk.shared::cluster.global.mbarrier::complete_tx::bytes [%0], [%1], %2, [%3];"
                 :: "r"(dst), "l"(src), "r"(bytes), "r"(bar) : "memory");
}
__device__ __forceinline__ void bulk_kv(uint32_t dst, const void* src, uint32_t bytes, uint32_t bar) {
    uint64_t pol; asm volatile("createpolicy.fractional.L2::evict_first.b64 %0, 1.0;" : "=l"(pol));
    asm volatile("cp.async.bulk.shared::cluster.global.mbarrier::complete_tx::bytes.L2::cache_hint [%0], [%1], %2, [%3], %4;"
                 :: "r"(dst), "l"(src), "r"(bytes), "r"(bar), "l"(pol) : "memory");
}
__device__ __forceinline__ uint4 lds128(uint32_t addr) {
    uint4 v;
    asm volatile("ld.shared.v4.u32 {%0,%1,%2,%3}, [%4];" : "=r"(v.x), "=r"(v.y), "=r"(v.z), "=r"(v.w) : "r"(addr) : "memory");
    return v;
}
__device__ __forceinline__ uint4 ldg128_nc(const void* p) {
    uint4 v;
    asm volatile("ld.global.nc.L1::no_allocate.v4.u32 {%0,%1,%2,%3}, [%4];" : "=r"(v.x), "=r"(v.y), "=r"(v.z), "=r"(v.w) : "l"(p));
    return v;
}
__device__ __forceinline__ uint32_t mapa(uint32_t addr, uint32_t rank) {
    uint32_t r; asm volatile("mapa.shared::cluster.u32 %0, %1, %2;" : "=r"(r) : "r"(addr), "r"(rank)); return r;
}
__device__ __forceinline__ void st_async_b32(uint32_t addr, uint32_t v, uint32_t bar) {
    asm volatile("st.async.shared::cluster.mbarrier::complete_tx::bytes.b32 [%0], %1, [%2];" :: "r"(addr), "r"(v), "r"(bar) : "memory");
}
__device__ __forceinline__ void st_async_v2(uint32_t addr, float a, float b, uint32_t bar) {
    asm volatile("st.async.shared::cluster.mbarrier::complete_tx::bytes.v2.f32 [%0], {%1, %2}, [%3];" :: "r"(addr), "f"(a), "f"(b), "r"(bar) : "memory");
}
__device__ __forceinline__ void st_async_v4(uint32_t addr, float a, float b, float c, float d, uint32_t bar) {
    asm volatile("st.async.shared::cluster.mbarrier::complete_tx::bytes.v4.f32 [%0], {%1, %2, %3, %4}, [%5];"
                 :: "r"(addr), "f"(a), "f"(b), "f"(c), "f"(d), "r"(bar) : "memory");
}
__device__ __forceinline__ uint32_t atom_inc_cluster(uint32_t addr) {
    uint32_t o; asm volatile("atom.relaxed.cluster.shared::cluster.add.u32 %0, [%1], 1;" : "=r"(o) : "r"(addr) : "memory"); return o;
}
__device__ __forceinline__ void cluster_arrive_relaxed() { asm volatile("barrier.cluster.arrive.relaxed.aligned;" ::: "memory"); }
__device__ __forceinline__ void cluster_wait()   { asm volatile("barrier.cluster.wait.acquire.aligned;" ::: "memory"); }

__device__ __forceinline__ float bf_lo(uint32_t x) { return __uint_as_float(x << 16); }
__device__ __forceinline__ float bf_hi(uint32_t x) { return __uint_as_float(x & 0xffff0000u); }
__device__ __forceinline__ float bf_round(float x) { return __bfloat162float(__float2bfloat16_rn(x)); }

__device__ __forceinline__ void unpack8(const uint4& v, float (&f)[8]) {
    f[0] = bf_lo(v.x); f[1] = bf_hi(v.x); f[2] = bf_lo(v.y); f[3] = bf_hi(v.y);
    f[4] = bf_lo(v.z); f[5] = bf_hi(v.z); f[6] = bf_lo(v.w); f[7] = bf_hi(v.w);
}

__device__ __forceinline__ void mma_bf16(float (&c)[4], uint32_t a0, uint32_t a1, uint32_t a2, uint32_t a3,
                                         uint32_t b0, uint32_t b1) {
    asm volatile("mma.sync.aligned.m16n8k16.row.col.f32.bf16.bf16.f32 {%0,%1,%2,%3}, {%4,%5,%6,%7}, {%8,%9}, {%0,%1,%2,%3};"
                 : "+f"(c[0]), "+f"(c[1]), "+f"(c[2]), "+f"(c[3])
                 : "r"(a0), "r"(a1), "r"(a2), "r"(a3), "r"(b0), "r"(b1));
}

struct Params {
    const __nv_bfloat16* x[2];
    const __nv_bfloat16* k[2];
    const __nv_bfloat16* v[2];
    const __nv_bfloat16* wq[2];
    const __nv_bfloat16* wo[2];
    __nv_bfloat16* out;
};

__global__ void __cluster_dims__(2, 1, 1) __launch_bounds__(THREADS, 1)
fused_decode_kernel(const Params P) {
    extern __shared__ __align__(128) unsigned char smem[];
    const uint32_t sbase = smem_u32(smem);
    const int tid  = threadIdx.x;
    const int warp = tid >> 5;
    const int lane = tid & 31;

    const int cta = blockIdx.x;
    STAMP(tid == 0, 0);
    const int p   = cta >> 6;
    const int h   = (cta >> 1) & 31;
    const int r   = cta & 1;

    const __nv_bfloat16* g_x  = p ? P.x[1]  : P.x[0];
    const __nv_bfloat16* g_k  = p ? P.k[1]  : P.k[0];
    const __nv_bfloat16* g_v  = p ? P.v[1]  : P.v[0];
    const __nv_bfloat16* g_wq = p ? P.wq[1] : P.wq[0];
    const __nv_bfloat16* g_wo = p ? P.wo[1] : P.wo[0];

    float* s_red = reinterpret_cast<float*>(smem + SM_ST);
    const float* s_st = reinterpret_cast<const float*>(smem + SM_ST);
    const float* s_ml = reinterpret_cast<const float*>(smem + SM_ML);

    const uint32_t qbar  = sbase + SM_BAR + NSW * 2 * NST * 8;
    const uint32_t obar  = qbar + 8;
    const uint32_t wobar = qbar + 16;
    if (tid == NSW * 32) {
        mbar_init(qbar, 1); mbar_init(obar, 1); mbar_init(wobar, 1);
        *reinterpret_cast<volatile uint32_t*>(smem + SM_CNT) = 16 * NST;
        asm volatile("fence.mbarrier_init.release.cluster;" ::: "memory");
        asm volatile("fence.acq_rel.cluster;" ::: "memory");
        asm volatile("fence.proxy.async.shared::cta;" ::: "memory");
        mbar_expect_tx(wobar, 64 * D_ * 2);
        mbar_expect_tx(qbar, 4 * DH_ * 2);
        mbar_expect_tx(obar, 16 * 4 * (64 + 2) * 4);
    }
    __syncwarp();
    cluster_arrive_relaxed();

    const int g = lane >> 2, t = lane & 3;
    uint4 wreg[16];
    uint32_t xa[8];
    {
        const __nv_bfloat16* wp = g_wq + (size_t)(warp * 64 + 2 * t) * HD_ + h * DH_ + r * 64 + g * 8;
        #pragma unroll
        for (int j = 0; j < 4; ++j) {
            wreg[j * 4 + 0] = ldg128_nc(wp + (size_t)(j * 16 + 0) * HD_);
            wreg[j * 4 + 1] = ldg128_nc(wp + (size_t)(j * 16 + 1) * HD_);
            wreg[j * 4 + 2] = ldg128_nc(wp + (size_t)(j * 16 + 8) * HD_);
            wreg[j * 4 + 3] = ldg128_nc(wp + (size_t)(j * 16 + 9) * HD_);
        }
        const uint32_t* xp = reinterpret_cast<const uint32_t*>(g_x + (g & 3) * D_ + warp * 64 + 2 * t);
        #pragma unroll
        for (int j = 0; j < 4; ++j) {
            xa[j * 2 + 0] = (g < 4) ? __ldg(xp + j * 8)     : 0u;
            xa[j * 2 + 1] = (g < 4) ? __ldg(xp + j * 8 + 4) : 0u;
        }
    }

    const uint32_t kbuf = sbase + SM_RING + warp * (2 * NST * UBYTES);
    const uint32_t vbuf = kbuf + NST * UBYTES;
    const uint32_t kbar = sbase + SM_BAR + warp * (2 * NST * 8);
    const uint32_t vbar = kbar + NST * 8;
    const uint32_t gw = r * NSW + warp;
    const unsigned char* kg = reinterpret_cast<const unsigned char*>(g_k + ((size_t)h * SK_ + (SK_ - W_)) * DH_);
    const unsigned char* vg = reinterpret_cast<const unsigned char*>(g_v + ((size_t)h * SK_ + (SK_ - W_)) * DH_);
    auto unit_off = [](uint32_t u) -> size_t {
        return (size_t)(u / UPP) * ((size_t)H_ * SK_ * DH_ * 2) + (size_t)(u % UPP) * UBYTES;
    };
    if (warp < NSW) {
        if (lane == 0) {
            #pragma unroll
            for (int s = 0; s < NST; ++s) { mbar_init(kbar + s * 8, 1); mbar_init(vbar + s * 8, 1); }
            asm volatile("fence.mbarrier_init.release.cluster;" ::: "memory");
            asm volatile("fence.proxy.async.shared::cta;" ::: "memory");
            #pragma unroll
            for (int s = 0; s < NST; ++s) {
                mbar_expect_tx(kbar + s * 8, UBYTES);
                bulk_kv(kbuf + s * UBYTES, kg + (size_t)(gw + 16 * s) * UBYTES, UBYTES, kbar + s * 8);
                mbar_expect_tx(vbar + s * 8, UBYTES);
                bulk_kv(vbuf + s * UBYTES, vg + (size_t)(gw + 16 * s) * UBYTES, UBYTES, vbar + s * 8);
            }
        }
        __syncwarp();
    }
    unsigned tag;
    asm volatile("ld.relaxed.gpu.global.u32 %0, [%1];" : "=r"(tag) : "l"(&g_epoch[cta]) : "memory");
    tag += 1u;

    {
        float c[8][4];
        #pragma unroll
        for (int e = 0; e < 8; ++e) { c[e][0] = c[e][1] = c[e][2] = c[e][3] = 0.f; }
        #pragma unroll
        for (int j = 0; j < 4; ++j) {
            const uint4 x0 = wreg[j * 4 + 0], x1 = wreg[j * 4 + 1], x2 = wreg[j * 4 + 2], x3 = wreg[j * 4 + 3];
            const uint32_t w0[4] = {x0.x, x0.y, x0.z, x0.w};
            const uint32_t w1[4] = {x1.x, x1.y, x1.z, x1.w};
            const uint32_t w2[4] = {x2.x, x2.y, x2.z, x2.w};
            const uint32_t w3[4] = {x3.x, x3.y, x3.z, x3.w};
            #pragma unroll
            for (int e = 0; e < 8; ++e) {
                const uint32_t sel = (e & 1) ? 0x7632u : 0x5410u;
                const uint32_t b0r = __byte_perm(w0[e >> 1], w1[e >> 1], sel);
                const uint32_t b1r = __byte_perm(w2[e >> 1], w3[e >> 1], sel);
                mma_bf16(c[e], xa[j * 2], 0u, xa[j * 2 + 1], 0u, b0r, b1r);
            }
        }
        if (g < 4) {
            float* dst = s_red + (warp * 4 + g) * 64 + t * 16;
            *reinterpret_cast<float4*>(dst)      = make_float4(c[0][0], c[1][0], c[2][0], c[3][0]);
            *reinterpret_cast<float4*>(dst + 4)  = make_float4(c[4][0], c[5][0], c[6][0], c[7][0]);
            *reinterpret_cast<float4*>(dst + 8)  = make_float4(c[0][1], c[1][1], c[2][1], c[3][1]);
            *reinterpret_cast<float4*>(dst + 12) = make_float4(c[4][1], c[5][1], c[6][1], c[7][1]);
        }
    }
    if (warp == NSW) {
        const unsigned char* src = reinterpret_cast<const unsigned char*>(g_wo + (size_t)(h * DH_ + r * 64) * D_);
        #pragma unroll
        for (int i = 0; i < 2; ++i) {
            const int row = lane + i * 32;
            bulk_g2s(sbase + SM_WOS + row * WO_STRIDE, src + (size_t)row * (D_ * 2), D_ * 2, wobar);
        }
    }
    __syncthreads();
    STAMP(tid == 0, 16 + 2);
    cluster_wait();
    STAMP(tid == 0, 16 + 3);
    if (tid < 128) {
        const int b = tid >> 5, c2 = (tid & 31) * 2;
        float s0 = 0.f, s1 = 0.f;
        #pragma unroll
        for (int w = 0; w < 10; ++w) {
            const float2 v2 = *reinterpret_cast<const float2*>(s_red + w * 256 + b * 64 + c2);
            s0 += v2.x; s1 += v2.y;
        }
        const __nv_bfloat162 qb = __floats2bfloat162_rn(s0, s1);
        const uint32_t dst = sbase + SM_QS + (b * DH_ + r * 64 + c2) * 2;
        st_async_b32(mapa(dst, 0u), *reinterpret_cast<const uint32_t*>(&qb), mapa(qbar, 0u));
        st_async_b32(mapa(dst, 1u), *reinterpret_cast<const uint32_t*>(&qb), mapa(qbar, 1u));
    }

    const int hl = lane & 15;
    const int hf = lane >> 4;
    const float scale = 0.08838834764831845f;
    const float LOG2E = 1.4426950408889634f;
    float q[8], acc[8];
    float m = -INFINITY, l = 0.f;
    #pragma unroll
    for (int e = 0; e < 8; ++e) { acc[e] = 0.f; q[e] = 0.f; }
    uint32_t idA = NUNITS, idB = NUNITS, nid = NUNITS, cur = 0;
    uint32_t slot = 0, ph = 0;
    const uint32_t cnt_addr = mapa(sbase + SM_CNT, 0u);
    if (warp < NSW) {
        idA = gw; idB = gw + 16;
        if (lane == 0) nid = atom_inc_cluster(cnt_addr);
        mbar_wait(qbar, 0);
        STAMP(tid == 0, 1);
        unpack8(lds128(sbase + SM_QS + hl * 16), q);
    }
    auto push_state = [&](uint32_t b) {
        #pragma unroll
        for (int e = 0; e < 8; ++e) acc[e] += __shfl_xor_sync(0xffffffffu, acc[e], 16);
        #pragma unroll
        for (int o = 16; o >= 1; o >>= 1) l += __shfl_xor_sync(0xffffffffu, l, o);
        if (hf == 0) {
            const uint32_t dr = (uint32_t)hl >> 3;
            const uint32_t a = mapa(sbase + SM_ST + ((gw * 4 + b) * 64 + (hl & 7) * 8) * 4, dr);
            const uint32_t bar = mapa(obar, dr);
            st_async_v4(a,      acc[0], acc[1], acc[2], acc[3], bar);
            st_async_v4(a + 16, acc[4], acc[5], acc[6], acc[7], bar);
        } else if (hl < 2) {
            st_async_v2(mapa(sbase + SM_ML + (gw * 4 + b) * 8, (uint32_t)hl), m, l * 0.5f, mapa(obar, (uint32_t)hl));
        }
        #pragma unroll
        for (int e = 0; e < 8; ++e) acc[e] = 0.f;
        m = -INFINITY; l = 0.f;
    };

    uint32_t bf0[4][8], bf1[4][8];
    #pragma unroll 1
    for (int stage = 0; stage < 2; ++stage) {
        const uint32_t lim = stage ? NUNITS : 3 * UPP;
        #pragma unroll 1
        while (idA < lim) {
            const uint32_t pr = idA / UPP;
            if (pr != cur) {
                #pragma unroll 1
                for (; cur < pr; ++cur) push_state(cur);
                unpack8(lds128(sbase + SM_QS + (pr * DH_ + hl * 8) * 2), q);
            }
            mbar_wait(kbar + slot * 8, ph);
            float v[8];
            {
                const uint32_t ka = kbuf + slot * UBYTES + lane * 16;
                #pragma unroll
                for (int s = 0; s < 8; ++s) {
                    uint4 x = lds128(ka + s * 512);
                    float f[8]; unpack8(x, f);
                    float d = f[0] * q[0];
                    #pragma unroll
                    for (int e = 1; e < 8; ++e) d = fmaf(f[e], q[e], d);
                    v[s] = d;
                }
            }
            const uint32_t n = __shfl_sync(0xffffffffu, nid, 0);
            const size_t noff = unit_off(n);
            if (lane == 0 && n < NUNITS) {
                mbar_expect_tx(kbar + slot * 8, UBYTES);
                bulk_kv(kbuf + slot * UBYTES, kg + noff, UBYTES, kbar + slot * 8);
                nid = atom_inc_cluster(cnt_addr);
            }
            float r4[4], r2[2], r1;
            {
                const bool up = lane & 8;
                #pragma unroll
                for (int j = 0; j < 4; ++j) {
                    float snd = up ? v[j] : v[j + 4];
                    float kep = up ? v[j + 4] : v[j];
                    r4[j] = kep + __shfl_xor_sync(0xffffffffu, snd, 8);
                }
            }
            {
                const bool up = lane & 4;
                #pragma unroll
                for (int j = 0; j < 2; ++j) {
                    float snd = up ? r4[j] : r4[j + 2];
                    float kep = up ? r4[j + 2] : r4[j];
                    r2[j] = kep + __shfl_xor_sync(0xffffffffu, snd, 4);
                }
            }
            {
                const bool up = lane & 2;
                float snd = up ? r2[0] : r2[1];
                float kep = up ? r2[1] : r2[0];
                r1 = kep + __shfl_xor_sync(0xffffffffu, snd, 2);
            }
            r1 += __shfl_xor_sync(0xffffffffu, r1, 1);
            float sc = bf_round(bf_round(r1) * scale);
            float mx = sc;
            #pragma unroll
            for (int o = 16; o >= 2; o >>= 1) mx = fmaxf(mx, __shfl_xor_sync(0xffffffffu, mx, o));
            if (mx > m) {
                const float corr = exp2f((m - mx) * LOG2E);
                l *= corr;
                #pragma unroll
                for (int e = 0; e < 8; ++e) acc[e] *= corr;
                m = mx;
            }
            const float pv = exp2f((sc - m) * LOG2E);
            l += pv;

            mbar_wait(vbar + slot * 8, ph);
            {
                const uint32_t va = vbuf + slot * UBYTES + lane * 16;
                #pragma unroll
                for (int s = 0; s < 8; ++s) {
                    const float pk = __shfl_sync(0xffffffffu, pv, (lane & 16) + 2 * s);
                    uint4 x = lds128(va + s * 512);
                    float f[8]; unpack8(x, f);
                    #pragma unroll
                    for (int e = 0; e < 8; ++e) acc[e] = fmaf(pk, f[e], acc[e]);
                }
            }
            __syncwarp();
            if (lane == 0 && n < NUNITS) {
                mbar_expect_tx(vbar + slot * 8, UBYTES);
                bulk_kv(vbuf + slot * UBYTES, vg + noff, UBYTES, vbar + slot * 8);
            }
            idA = idB; idB = n;
            slot ^= 1u; ph ^= (slot ^ 1u);
        }
        if (stage == 0) {
            mbar_wait(wobar, 0);
            #pragma unroll
            for (int j = 0; j < 4; ++j) {
                const uint32_t wa = sbase + SM_WOS + (j * 16 + 2 * t) * WO_STRIDE + (warp * 64 + g * 8) * 2;
                const uint4 x0 = lds128(wa), x1 = lds128(wa + WO_STRIDE), x2 = lds128(wa + 8 * WO_STRIDE), x3 = lds128(wa + 9 * WO_STRIDE);
                const uint32_t w0[4] = {x0.x, x0.y, x0.z, x0.w};
                const uint32_t w1[4] = {x1.x, x1.y, x1.z, x1.w};
                const uint32_t w2[4] = {x2.x, x2.y, x2.z, x2.w};
                const uint32_t w3[4] = {x3.x, x3.y, x3.z, x3.w};
                #pragma unroll
                for (int e = 0; e < 8; ++e) {
                    const uint32_t sel = (e & 1) ? 0x7632u : 0x5410u;
                    bf0[j][e] = __byte_perm(w0[e >> 1], w1[e >> 1], sel);
                    bf1[j][e] = __byte_perm(w2[e >> 1], w3[e >> 1], sel);
                }
            }
        }
    }
    if (warp < NSW) {
        STAMP(lane == 0, 8 + warp);
        #pragma unroll 1
        for (; cur < 4; ++cur) push_state(cur);
    }
    mbar_wait(obar, 0);
    STAMP(tid == 0, 2);

    if (tid < 256) {
        const int b = tid >> 6, d = tid & 63;
        float M = -INFINITY;
        #pragma unroll
        for (int w = 0; w < 16; ++w) M = fmaxf(M, s_ml[(w * 4 + b) * 2]);
        float L = 0.f, o = 0.f;
        #pragma unroll
        for (int w = 0; w < 16; ++w) {
            const float2 ml = *reinterpret_cast<const float2*>(s_ml + (w * 4 + b) * 2);
            const float c = exp2f((ml.x - M) * LOG2E);
            L = fmaf(ml.y, c, L);
            o = fmaf(s_st[(w * 4 + b) * 64 + d], c, o);
        }
        const __nv_bfloat16 ob = __float2bfloat16_rn(o / L);
        *reinterpret_cast<__nv_bfloat16*>(smem + SM_QS + (b * 64 + d) * 2) = ob;
    }
    STAMP(tid == 0, 6);
    __syncthreads();
    STAMP(tid == 0, 7);

    {
        float c[4][4];
        #pragma unroll
        for (int e = 0; e < 4; ++e) { c[e][0] = c[e][1] = c[e][2] = c[e][3] = 0.f; }
        #pragma unroll
        for (int ks = 0; ks < 4; ++ks) {
            uint32_t b0 = 0, b1 = 0;
            if (g < 4) {
                asm volatile("ld.shared.u32 %0, [%1];" : "=r"(b0) : "r"(sbase + SM_QS + (g * 64 + ks * 16 + 2 * t) * 2) : "memory");
                asm volatile("ld.shared.u32 %0, [%1];" : "=r"(b1) : "r"(sbase + SM_QS + (g * 64 + ks * 16 + 2 * t + 8) * 2) : "memory");
            }
            #pragma unroll
            for (int e = 0; e < 4; ++e) mma_bf16(c[e], bf0[ks][e], bf0[ks][e + 4], bf1[ks][e], bf1[ks][e + 4], b0, b1);
        }
        float* tile = s_red + warp * 256;
        if (t < 2) {
            float* dst = tile + 2 * t * 64 + g * 8;
            *reinterpret_cast<float4*>(dst)      = make_float4(c[0][0], c[1][0], c[2][0], c[3][0]);
            *reinterpret_cast<float4*>(dst + 4)  = make_float4(c[0][2], c[1][2], c[2][2], c[3][2]);
            *reinterpret_cast<float4*>(dst + 64) = make_float4(c[0][1], c[1][1], c[2][1], c[3][1]);
            *reinterpret_cast<float4*>(dst + 68) = make_float4(c[0][3], c[1][3], c[2][3], c[3][3]);
        }
        __syncwarp();
        {
            unsigned long long* dst = g_part + (size_t)cta * 4 * D_ + warp * 64 + lane * 2;
            const unsigned long long hi = (unsigned long long)tag << 32;
            #pragma unroll
            for (int b = 0; b < 4; ++b) {
                const float2 v2 = *reinterpret_cast<const float2*>(tile + b * 64 + lane * 2);
                asm volatile("st.relaxed.gpu.global.v2.b64 [%0], {%1, %2};"
                             :: "l"(dst + b * D_), "l"(hi | __float_as_uint(v2.x)), "l"(hi | __float_as_uint(v2.y)) : "memory");
            }
        }
    }
    {
        __syncthreads();
        if (tid == 0) {
            asm volatile("red.relaxed.gpu.global.add.u32 [%0], 1;" :: "l"(&g_cnt) : "memory");
            const unsigned target = tag * (unsigned)NCTA;
            unsigned cur2;
            int spins = 0;
            do {
                asm volatile("ld.relaxed.gpu.global.u32 %0, [%1];" : "=r"(cur2) : "l"(&g_cnt) : "memory");
                if (++spins > (1 << 24)) __trap();
            } while ((int)(cur2 - target) < 0);
        }
        __syncthreads();
    }
    STAMP(tid == 0, 3);

    {
        const int row = cta >> 4;
        const int pp  = row >> 2, bb = row & 3;
        const int n   = (cta & 15) * 40 + warp * 4 + t;
        const unsigned long long* src = g_part + ((size_t)(pp * 64 + g * 8) * 4 + bb) * D_ + n;
        unsigned long long vals[8];
        #pragma unroll
        for (int i = 0; i < 8; ++i) vals[i] = 0ull;
        #pragma unroll 1
        for (int spin = 0; ; ++spin) {
            #pragma unroll
            for (int i = 0; i < 8; ++i)
                if ((unsigned)(vals[i] >> 32) != tag)
                    asm volatile("ld.relaxed.gpu.global.b64 %0, [%1];" : "=l"(vals[i]) : "l"(src + (size_t)i * 4 * D_) : "memory");
            bool ok = true;
            #pragma unroll
            for (int i = 0; i < 8; ++i) ok = ok && ((unsigned)(vals[i] >> 32) == tag);
            if (ok) break;
            if (spin > (1 << 22)) __trap();
        }
        STAMP(tid == 0, 4);
        float s = 0.f;
        #pragma unroll
        for (int i = 0; i < 8; ++i) s += __uint_as_float((unsigned)vals[i]);
        __syncwarp();
        s += __shfl_xor_sync(0xffffffffu, s, 4);
        s += __shfl_xor_sync(0xffffffffu, s, 8);
        s += __shfl_xor_sync(0xffffffffu, s, 16);
        if (g == 0) P.out[bb * (2 * D_) + pp * D_ + n] = __float2bfloat16_rn(s);
    }
    if (tid == 0) g_epoch[cta] = tag;
    STAMP(tid == 0, 5);
}

}

extern "C" void kernel_launch(void* const* d_in, const int* in_sizes, int n_in,
                              void* d_out, int out_size) {
    (void)in_sizes; (void)n_in; (void)out_size;
    static bool attr_set = false;
    if (!attr_set) {
        cudaFuncSetAttribute(fused_decode_kernel, cudaFuncAttributeMaxDynamicSharedMemorySize, SM_TOTAL);
        attr_set = true;
    }
    Params P;
    for (int p = 0; p < 2; ++p) {
        P.x[p]  = (const __nv_bfloat16*)d_in[p * 5 + 0];
        P.k[p]  = (const __nv_bfloat16*)d_in[p * 5 + 1];
        P.v[p]  = (const __nv_bfloat16*)d_in[p * 5 + 2];
        P.wq[p] = (const __nv_bfloat16*)d_in[p * 5 + 3];
        P.wo[p] = (const __nv_bfloat16*)d_in[p * 5 + 4];
    }
    P.out = (__nv_bfloat16*)d_out;
    fused_decode_kernel<<<NCTA, THREADS, SM_TOTAL>>>(P);
}
```

```cpp
#include <cuda_runtime.h>
#include <cuda_bf16.h>
#include <stdint.h>

namespace {

constexpr int D_      = 640;
constexpr int H_      = 32;
constexpr int SK_     = 8192;
constexpr int DH_     = 128;
constexpr int W_      = 2048;
constexpr int HD_     = H_ * DH_;

constexpr int NCTA    = 128;
constexpr int NSW     = 8;
constexpr int THREADS = 320;
constexpr int UKEYS   = 16;
constexpr int UBYTES  = UKEYS * DH_ * 2;
constexpr int NST     = 2;
constexpr uint32_t UPP = W_ / UKEYS;
constexpr uint32_t NUNITS = 4 * UPP;
constexpr int WO_STRIDE = D_ * 2 + 16;
constexpr uint32_t WO_TRIG = 10;
constexpr uint32_t WO_GATE = 48;
constexpr uint32_t HINT_K  = 16;

constexpr int SM_RING   = 0;
constexpr int SM_WOS    = SM_RING + NSW * 2 * NST * UBYTES;
constexpr int SM_ST     = SM_WOS + 64 * WO_STRIDE;
constexpr int SM_ML     = SM_ST + 16 * 4 * 64 * 4;
constexpr int SM_QS     = SM_ML + 16 * 4 * 2 * 4;
constexpr int SM_BAR    = SM_QS + 4 * DH_ * 2;
constexpr int SM_CNT    = SM_BAR + (NSW * 2 * NST + 6) * 8;
constexpr int SM_TOTAL  = SM_CNT + 16;
static_assert(SM_TOTAL <= 232448, "smem");

__device__ unsigned long long g_part[NCTA * 4 * D_];
__device__ unsigned           g_epoch[NCTA];
__device__ unsigned           g_trig;
__device__ unsigned           g_cnt;

#define STAMP(cond, slot) do {} while (0)

__device__ __forceinline__ uint32_t smem_u32(const void* p) {
    return (uint32_t)__cvta_generic_to_shared(p);
}
__device__ __forceinline__ void mbar_init(uint32_t bar, uint32_t cnt) {
    asm volatile("mbarrier.init.shared::cta.b64 [%0], %1;" :: "r"(bar), "r"(cnt) : "memory");
}
__device__ __forceinline__ void mbar_expect_tx(uint32_t bar, uint32_t bytes) {
    asm volatile("mbarrier.arrive.expect_tx.shared::cta.b64 _, [%0], %1;" :: "r"(bar), "r"(bytes) : "memory");
}
__device__ __forceinline__ bool mbar_try_wait(uint32_t bar, uint32_t parity) {
    uint32_t ok;
    asm volatile("{\n\t.reg .pred p;\n\t"
                 "mbarrier.try_wait.parity.shared::cta.b64 p, [%1], %2;\n\t"
                 "selp.u32 %0, 1, 0, p;\n\t}"
                 : "=r"(ok) : "r"(bar), "r"(parity) : "memory");
    return ok != 0;
}
__device__ __forceinline__ void mbar_wait(uint32_t bar, uint32_t parity) {
    #pragma unroll 1
    for (int i = 0; i < (1 << 22); ++i)
        if (mbar_try_wait(bar, parity)) return;
    __trap();
}
__device__ __forceinline__ void bulk_g2s(uint32_t dst, const void* src, uint32_t bytes, uint32_t bar) {
    asm volatile("cp.async.bulk.shared::cluster.global.mbarrier::complete_tx::bytes [%0], [%1], %2, [%3];"
                 :: "r"(dst), "l"(src), "r"(bytes), "r"(bar) : "memory");
}
__device__ __forceinline__ void bulk_kv(uint32_t dst, const void* src, uint32_t bytes, uint32_t bar) {
    uint64_t pol; asm volatile("createpolicy.fractional.L2::evict_first.b64 %0, 1.0;" : "=l"(pol));
    asm volatile("cp.async.bulk.shared::cluster.global.mbarrier::complete_tx::bytes.L2::cache_hint [%0], [%1], %2, [%3], %4;"
                 :: "r"(dst), "l"(src), "r"(bytes), "r"(bar), "l"(pol) : "memory");
}
__device__ __forceinline__ uint4 lds128(uint32_t addr) {
    uint4 v;
    asm volatile("ld.shared.v4.u32 {%0,%1,%2,%3}, [%4];" : "=r"(v.x), "=r"(v.y), "=r"(v.z), "=r"(v.w) : "r"(addr) : "memory");
    return v;
}
__device__ __forceinline__ uint4 ldg128_nc(const void* p) {
    uint4 v;
    asm volatile("ld.global.nc.L1::no_allocate.v4.u32 {%0,%1,%2,%3}, [%4];" : "=r"(v.x), "=r"(v.y), "=r"(v.z), "=r"(v.w) : "l"(p));
    return v;
}
__device__ __forceinline__ uint32_t mapa(uint32_t addr, uint32_t rank) {
    uint32_t r; asm volatile("mapa.shared::cluster.u32 %0, %1, %2;" : "=r"(r) : "r"(addr), "r"(rank)); return r;
}
__device__ __forceinline__ void st_async_b32(uint32_t addr, uint32_t v, uint32_t bar) {
    asm volatile("st.async.shared::cluster.mbarrier::complete_tx::bytes.b32 [%0], %1, [%2];" :: "r"(addr), "r"(v), "r"(bar) : "memory");
}
__device__ __forceinline__ void st_async_v2(uint32_t addr, float a, float b, uint32_t bar) {
    asm volatile("st.async.shared::cluster.mbarrier::complete_tx::bytes.v2.f32 [%0], {%1, %2}, [%3];" :: "r"(addr), "f"(a), "f"(b), "r"(bar) : "memory");
}
__device__ __forceinline__ void st_async_v4(uint32_t addr, float a, float b, float c, float d, uint32_t bar) {
    asm volatile("st.async.shared::cluster.mbarrier::complete_tx::bytes.v4.f32 [%0], {%1, %2, %3, %4}, [%5];"
                 :: "r"(addr), "f"(a), "f"(b), "f"(c), "f"(d), "r"(bar) : "memory");
}
__device__ __forceinline__ uint32_t atom_inc_cluster(uint32_t addr) {
    uint32_t o; asm volatile("atom.relaxed.cluster.shared::cluster.add.u32 %0, [%1], 1;" : "=r"(o) : "r"(addr) : "memory"); return o;
}
__device__ __forceinline__ void cluster_arrive_relaxed() { asm volatile("barrier.cluster.arrive.relaxed.aligned;" ::: "memory"); }
__device__ __forceinline__ void cluster_wait()   { asm volatile("barrier.cluster.wait.acquire.aligned;" ::: "memory"); }

__device__ __forceinline__ float bf_lo(uint32_t x) { return __uint_as_float(x << 16); }
__device__ __forceinline__ float bf_hi(uint32_t x) { return __uint_as_float(x & 0xffff0000u); }
__device__ __forceinline__ float bf_round(float x) { return __bfloat162float(__float2bfloat16_rn(x)); }

__device__ __forceinline__ void unpack8(const uint4& v, float (&f)[8]) {
    f[0] = bf_lo(v.x); f[1] = bf_hi(v.x); f[2] = bf_lo(v.y); f[3] = bf_hi(v.y);
    f[4] = bf_lo(v.z); f[5] = bf_hi(v.z); f[6] = bf_lo(v.w); f[7] = bf_hi(v.w);
}

__device__ __forceinline__ void mma_bf16(float (&c)[4], uint32_t a0, uint32_t a1, uint32_t a2, uint32_t a3,
                                         uint32_t b0, uint32_t b1) {
    asm volatile("mma.sync.aligned.m16n8k16.row.col.f32.bf16.bf16.f32 {%0,%1,%2,%3}, {%4,%5,%6,%7}, {%8,%9}, {%0,%1,%2,%3};"
                 : "+f"(c[0]), "+f"(c[1]), "+f"(c[2]), "+f"(c[3])
                 : "r"(a0), "r"(a1), "r"(a2), "r"(a3), "r"(b0), "r"(b1));
}

struct Params {
    const __nv_bfloat16* x[2];
    const __nv_bfloat16* k[2];
    const __nv_bfloat16* v[2];
    const __nv_bfloat16* wq[2];
    const __nv_bfloat16* wo[2];
    __nv_bfloat16* out;
};

__global__ void __cluster_dims__(2, 1, 1) __launch_bounds__(THREADS, 1)
fused_decode_kernel(const Params P) {
    extern __shared__ __align__(128) unsigned char smem[];
    const uint32_t sbase = smem_u32(smem);
    const int tid  = threadIdx.x;
    const int warp = tid >> 5;
    const int lane = tid & 31;

    const int cta = blockIdx.x;
    STAMP(tid == 0, 0);
    const int p   = cta >> 6;
    const int h   = (cta >> 1) & 31;
    const int r   = cta & 1;

    const __nv_bfloat16* g_x  = p ? P.x[1]  : P.x[0];
    const __nv_bfloat16* g_k  = p ? P.k[1]  : P.k[0];
    const __nv_bfloat16* g_v  = p ? P.v[1]  : P.v[0];
    const __nv_bfloat16* g_wq = p ? P.wq[1] : P.wq[0];
    const __nv_bfloat16* g_wo = p ? P.wo[1] : P.wo[0];

    float* s_red = reinterpret_cast<float*>(smem + SM_ST);
    const float* s_st = reinterpret_cast<const float*>(smem + SM_ST);
    const float* s_ml = reinterpret_cast<const float*>(smem + SM_ML);

    const uint32_t qbar  = sbase + SM_BAR + NSW * 2 * NST * 8;
    const uint32_t obar  = qbar + 8;
    const uint32_t wobar = qbar + 16;
    if (tid == NSW * 32) {
        mbar_init(qbar, 1); mbar_init(obar, 1);
        #pragma unroll
        for (int j = 0; j < 4; ++j) mbar_init(wobar + j * 8, 1);
        *reinterpret_cast<volatile uint32_t*>(smem + SM_CNT) = 16 * NST;
        *reinterpret_cast<volatile uint32_t*>(smem + SM_CNT + 4) = 0;
        *reinterpret_cast<volatile uint32_t*>(smem + SM_CNT + 8) = 0;
        asm volatile("fence.mbarrier_init.release.cluster;" ::: "memory");
        asm volatile("fence.acq_rel.cluster;" ::: "memory");
        asm volatile("fence.proxy.async.shared::cta;" ::: "memory");
        #pragma unroll
        for (int j = 0; j < 4; ++j) mbar_expect_tx(wobar + j * 8, 16 * D_ * 2);
        mbar_expect_tx(qbar, 4 * DH_ * 2);
        mbar_expect_tx(obar, 16 * 4 * (64 + 2) * 4);
    }
    __syncwarp();
    cluster_arrive_relaxed();

    const int g = lane >> 2, t = lane & 3;
    uint4 wreg[16];
    uint32_t xa[8];
    {
        const __nv_bfloat16* wp = g_wq + (size_t)(warp * 64 + 2 * t) * HD_ + h * DH_ + r * 64 + g * 8;
        #pragma unroll
        for (int j = 0; j < 4; ++j) {
            wreg[j * 4 + 0] = ldg128_nc(wp + (size_t)(j * 16 + 0) * HD_);
            wreg[j * 4 + 1] = ldg128_nc(wp + (size_t)(j * 16 + 1) * HD_);
            wreg[j * 4 + 2] = ldg128_nc(wp + (size_t)(j * 16 + 8) * HD_);
            wreg[j * 4 + 3] = ldg128_nc(wp + (size_t)(j * 16 + 9) * HD_);
        }
        const uint32_t* xp = reinterpret_cast<const uint32_t*>(g_x + (g & 3) * D_ + warp * 64 + 2 * t);
        #pragma unroll
        for (int j = 0; j < 4; ++j) {
            xa[j * 2 + 0] = (g < 4) ? __ldg(xp + j * 8)     : 0u;
            xa[j * 2 + 1] = (g < 4) ? __ldg(xp + j * 8 + 4) : 0u;
        }
    }

    const uint32_t kbuf = sbase + SM_RING + warp * (2 * NST * UBYTES);
    const uint32_t vbuf = kbuf + NST * UBYTES;
    const uint32_t kbar = sbase + SM_BAR + warp * (2 * NST * 8);
    const uint32_t vbar = kbar + NST * 8;
    const uint32_t gw = r * NSW + warp;
    const unsigned char* kg = reinterpret_cast<const unsigned char*>(g_k + ((size_t)h * SK_ + (SK_ - W_)) * DH_);
    const unsigned char* vg = reinterpret_cast<const unsigned char*>(g_v + ((size_t)h * SK_ + (SK_ - W_)) * DH_);
    auto unit_off = [](uint32_t u) -> size_t {
        return (size_t)(u / UPP) * ((size_t)H_ * SK_ * DH_ * 2) + (size_t)(u % UPP) * UBYTES;
    };
    if (warp < NSW) {
        if (lane == 0) {
            #pragma unroll
            for (int s = 0; s < NST; ++s) { mbar_init(kbar + s * 8, 1); mbar_init(vbar + s * 8, 1); }
            asm volatile("fence.mbarrier_init.release.cluster;" ::: "memory");
            asm volatile("fence.proxy.async.shared::cta;" ::: "memory");
            mbar_expect_tx(kbar, UBYTES);
            bulk_kv(kbuf, kg + (size_t)gw * UBYTES, UBYTES, kbar);
            mbar_expect_tx(vbar, UBYTES);
            bulk_kv(vbuf, vg + (size_t)gw * UBYTES, UBYTES, vbar);
        }
        __syncwarp();
    }
    unsigned tag;
    asm volatile("ld.relaxed.gpu.global.u32 %0, [%1];" : "=r"(tag) : "l"(&g_epoch[cta]) : "memory");
    tag += 1u;

    {
        float c[8][4];
        #pragma unroll
        for (int e = 0; e < 8; ++e) { c[e][0] = c[e][1] = c[e][2] = c[e][3] = 0.f; }
        #pragma unroll
        for (int j = 0; j < 4; ++j) {
            const uint4 x0 = wreg[j * 4 + 0], x1 = wreg[j * 4 + 1], x2 = wreg[j * 4 + 2], x3 = wreg[j * 4 + 3];
            const uint32_t w0[4] = {x0.x, x0.y, x0.z, x0.w};
            const uint32_t w1[4] = {x1.x, x1.y, x1.z, x1.w};
            const uint32_t w2[4] = {x2.x, x2.y, x2.z, x2.w};
            const uint32_t w3[4] = {x3.x, x3.y, x3.z, x3.w};
            #pragma unroll
            for (int e = 0; e < 8; ++e) {
                const uint32_t sel = (e & 1) ? 0x7632u : 0x5410u;
                const uint32_t b0r = __byte_perm(w0[e >> 1], w1[e >> 1], sel);
                const uint32_t b1r = __byte_perm(w2[e >> 1], w3[e >> 1], sel);
                mma_bf16(c[e], xa[j * 2], 0u, xa[j * 2 + 1], 0u, b0r, b1r);
            }
        }
        if (g < 4) {
            float* dst = s_red + (warp * 4 + g) * 64 + t * 16;
            *reinterpret_cast<float4*>(dst)      = make_float4(c[0][0], c[1][0], c[2][0], c[3][0]);
            *reinterpret_cast<float4*>(dst + 4)  = make_float4(c[4][0], c[5][0], c[6][0], c[7][0]);
            *reinterpret_cast<float4*>(dst + 8)  = make_float4(c[0][1], c[1][1], c[2][1], c[3][1]);
            *reinterpret_cast<float4*>(dst + 12) = make_float4(c[4][1], c[5][1], c[6][1], c[7][1]);
        }
    }
    __syncthreads();
    STAMP(tid == 0, 16 + 2);
    cluster_wait();
    STAMP(tid == 0, 16 + 3);
    if (tid < 128) {
        const int b = tid >> 5, c2 = (tid & 31) * 2;
        float s0 = 0.f, s1 = 0.f;
        #pragma unroll
        for (int w = 0; w < 10; ++w) {
            const float2 v2 = *reinterpret_cast<const float2*>(s_red + w * 256 + b * 64 + c2);
            s0 += v2.x; s1 += v2.y;
        }
        const __nv_bfloat162 qb = __floats2bfloat162_rn(s0, s1);
        const uint32_t dst = sbase + SM_QS + (b * DH_ + r * 64 + c2) * 2;
        st_async_b32(mapa(dst, 0u), *reinterpret_cast<const uint32_t*>(&qb), mapa(qbar, 0u));
        st_async_b32(mapa(dst, 1u), *reinterpret_cast<const uint32_t*>(&qb), mapa(qbar, 1u));
    }
    __syncthreads();
    if (warp < NSW && lane == 0) {
        mbar_expect_tx(kbar + 8, UBYTES);
        bulk_kv(kbuf + UBYTES, kg + (size_t)(gw + 16) * UBYTES, UBYTES, kbar + 8);
        mbar_expect_tx(vbar + 8, UBYTES);
        bulk_kv(vbuf + UBYTES, vg + (size_t)(gw + 16) * UBYTES, UBYTES, vbar + 8);
    }
    __syncwarp();

    const int hl = lane & 15;
    const int hf = lane >> 4;
    const float scale = 0.08838834764831845f;
    const float LOG2E = 1.4426950408889634f;
    float q[8], acc[8];
    float m = -INFINITY, l = 0.f;
    #pragma unroll
    for (int e = 0; e < 8; ++e) { acc[e] = 0.f; q[e] = 0.f; }
    uint32_t idA = NUNITS, idB = NUNITS, nid = NUNITS, cur = 0;
    uint32_t slot = 0, ph = 0;
    const uint32_t cnt_addr = mapa(sbase + SM_CNT, 0u);
    if (warp < NSW) {
        idA = gw; idB = gw + 16;
        if (lane == 0) nid = atom_inc_cluster(cnt_addr);
        mbar_wait(qbar, 0);
        STAMP(tid == 0, 1);
        unpack8(lds128(sbase + SM_QS + hl * 16), q);
    }
    auto push_state = [&](uint32_t b) {
        #pragma unroll
        for (int e = 0; e < 8; ++e) acc[e] += __shfl_xor_sync(0xffffffffu, acc[e], 16);
        #pragma unroll
        for (int o = 16; o >= 1; o >>= 1) l += __shfl_xor_sync(0xffffffffu, l, o);
        if (hf == 0) {
            const uint32_t dr = (uint32_t)hl >> 3;
            const uint32_t a = mapa(sbase + SM_ST + ((gw * 4 + b) * 64 + (hl & 7) * 8) * 4, dr);
            const uint32_t bar = mapa(obar, dr);
            st_async_v4(a,      acc[0], acc[1], acc[2], acc[3], bar);
            st_async_v4(a + 16, acc[4], acc[5], acc[6], acc[7], bar);
        } else if (hl < 2) {
            st_async_v2(mapa(sbase + SM_ML + (gw * 4 + b) * 8, (uint32_t)hl), m, l * 0.5f, mapa(obar, (uint32_t)hl));
        }
        #pragma unroll
        for (int e = 0; e < 8; ++e) acc[e] = 0.f;
        m = -INFINITY; l = 0.f;
    };

    {
        #pragma unroll 1
        while (idA < NUNITS) {
            const uint32_t pr = idA / UPP;
            if (pr != cur) {
                #pragma unroll 1
                for (; cur < pr; ++cur) push_state(cur);
                unpack8(lds128(sbase + SM_QS + (pr * DH_ + hl * 8) * 2), q);
            }
            mbar_wait(kbar + slot * 8, ph);
            float v[8];
            {
                const uint32_t ka = kbuf + slot * UBYTES + lane * 16;
                #pragma unroll
                for (int s = 0; s < 8; ++s) {
                    uint4 x = lds128(ka + s * 512);
                    float f[8]; unpack8(x, f);
                    float d = f[0] * q[0];
                    #pragma unroll
                    for (int e = 1; e < 8; ++e) d = fmaf(f[e], q[e], d);
                    v[s] = d;
                }
            }
            const uint32_t n = __shfl_sync(0xffffffffu, nid, 0);
            const size_t noff = unit_off(n);
            if (lane == 0 && n >= NUNITS) atomicAdd(reinterpret_cast<uint32_t*>(smem + SM_CNT + 4), 1u);
            if (lane == 0 && n < NUNITS) {
                mbar_expect_tx(kbar + slot * 8, UBYTES);
                bulk_kv(kbuf + slot * UBYTES, kg + noff, UBYTES, kbar + slot * 8);
                nid = atom_inc_cluster(cnt_addr);
            }
            float r4[4], r2[2], r1;
            {
                const bool up = lane & 8;
                #pragma unroll
                for (int j = 0; j < 4; ++j) {
                    float snd = up ? v[j] : v[j + 4];
                    float kep = up ? v[j + 4] : v[j];
                    r4[j] = kep + __shfl_xor_sync(0xffffffffu, snd, 8);
                }
            }
            {
                const bool up = lane & 4;
                #pragma unroll
                for (int j = 0; j < 2; ++j) {
                    float snd = up ? r4[j] : r4[j + 2];
                    float kep = up ? r4[j + 2] : r4[j];
                    r2[j] = kep + __shfl_xor_sync(0xffffffffu, snd, 4);
                }
            }
            {
                const bool up = lane & 2;
                float snd = up ? r2[0] : r2[1];
                float kep = up ? r2[1] : r2[0];
                r1 = kep + __shfl_xor_sync(0xffffffffu, snd, 2);
            }
            r1 += __shfl_xor_sync(0xffffffffu, r1, 1);
            float sc = bf_round(bf_round(r1) * scale);
            float mx = sc;
            #pragma unroll
            for (int o = 16; o >= 2; o >>= 1) mx = fmaxf(mx, __shfl_xor_sync(0xffffffffu, mx, o));
            if (mx > m) {
                const float corr = exp2f((m - mx) * LOG2E);
                l *= corr;
                #pragma unroll
                for (int e = 0; e < 8; ++e) acc[e] *= corr;
                m = mx;
            }
            const float pv = exp2f((sc - m) * LOG2E);
            l += pv;

            mbar_wait(vbar + slot * 8, ph);
            {
                const uint32_t va = vbuf + slot * UBYTES + lane * 16;
                #pragma unroll
                for (int s = 0; s < 8; ++s) {
                    const float pk = __shfl_sync(0xffffffffu, pv, (lane & 16) + 2 * s);
                    uint4 x = lds128(va + s * 512);
                    float f[8]; unpack8(x, f);
                    #pragma unroll
                    for (int e = 0; e < 8; ++e) acc[e] = fmaf(pk, f[e], acc[e]);
                }
            }
            __syncwarp();
            if (lane == 0 && n < NUNITS) {
                mbar_expect_tx(vbar + slot * 8, UBYTES);
                bulk_kv(vbuf + slot * UBYTES, vg + noff, UBYTES, vbar + slot * 8);
            }
            idA = idB; idB = n;
            slot ^= 1u; ph ^= (slot ^ 1u);
        }
    }
    if (warp < NSW) {
        STAMP(lane == 0, 8 + warp);
        #pragma unroll 1
        for (; cur < 4; ++cur) push_state(cur);
        if (lane == 0) atomicAdd(reinterpret_cast<uint32_t*>(smem + SM_CNT + 4), 1u);
    } else if (warp == NSW) {
        #pragma unroll 1
        for (int i = 0; i < (1 << 22); ++i) {
            if (*reinterpret_cast<volatile uint32_t*>(smem + SM_CNT + 4) >= WO_TRIG) break;
            __nanosleep(100);
        }
        if (lane == 0) asm volatile("red.relaxed.gpu.global.add.u32 [%0], 1;" :: "l"(&g_trig) : "memory");
        #pragma unroll 1
        for (int i = 0; i < (1 << 22); ++i) {
            if (*reinterpret_cast<volatile uint32_t*>(smem + SM_CNT + 8)) break;
            __nanosleep(100);
        }
        const unsigned char* src = reinterpret_cast<const unsigned char*>(g_wo + (size_t)(h * DH_ + r * 64) * D_);
        #pragma unroll
        for (int i = 0; i < 2; ++i) {
            const int row = lane + i * 32;
            bulk_g2s(sbase + SM_WOS + row * WO_STRIDE, src + (size_t)row * (D_ * 2), D_ * 2, wobar + (row >> 4) * 8);
        }
    } else {
        if (lane == 0) {
            const unsigned target = (tag - 1u) * (unsigned)NCTA + WO_GATE;
            #pragma unroll 1
            for (int i = 0; i < (1 << 20); ++i) {
                unsigned c; asm volatile("ld.relaxed.gpu.global.u32 %0, [%1];" : "=r"(c) : "l"(&g_trig) : "memory");
                if ((int)(c - target) >= 0) break;
                __nanosleep(400);
            }
            *reinterpret_cast<volatile uint32_t*>(smem + SM_CNT + 8) = 1;
        }
        __syncwarp();
    }
    uint32_t bf0[4][8], bf1[4][8];
    auto load_frags = [&](const int j) {
        const uint32_t wa = sbase + SM_WOS + (j * 16 + 2 * t) * WO_STRIDE + (warp * 64 + g * 8) * 2;
        const uint4 x0 = lds128(wa), x1 = lds128(wa + WO_STRIDE), x2 = lds128(wa + 8 * WO_STRIDE), x3 = lds128(wa + 9 * WO_STRIDE);
        const uint32_t w0[4] = {x0.x, x0.y, x0.z, x0.w};
        const uint32_t w1[4] = {x1.x, x1.y, x1.z, x1.w};
        const uint32_t w2[4] = {x2.x, x2.y, x2.z, x2.w};
        const uint32_t w3[4] = {x3.x, x3.y, x3.z, x3.w};
        #pragma unroll
        for (int e = 0; e < 8; ++e) {
            const uint32_t sel = (e & 1) ? 0x7632u : 0x5410u;
            bf0[j][e] = __byte_perm(w0[e >> 1], w1[e >> 1], sel);
            bf1[j][e] = __byte_perm(w2[e >> 1], w3[e >> 1], sel);
        }
    };
    auto combine = [&]() {
        const int b = tid >> 6, d = tid & 63;
        float M = -INFINITY;
        #pragma unroll
        for (int w = 0; w < 16; ++w) M = fmaxf(M, s_ml[(w * 4 + b) * 2]);
        float L = 0.f, o = 0.f;
        #pragma unroll
        for (int w = 0; w < 16; ++w) {
            const float2 ml = *reinterpret_cast<const float2*>(s_ml + (w * 4 + b) * 2);
            const float c = exp2f((ml.x - M) * LOG2E);
            L = fmaf(ml.y, c, L);
            o = fmaf(s_st[(w * 4 + b) * 64 + d], c, o);
        }
        const __nv_bfloat16 ob = __float2bfloat16_rn(o / L);
        *reinterpret_cast<__nv_bfloat16*>(smem + SM_QS + (b * 64 + d) * 2) = ob;
    };
    if (tid < 256) { mbar_wait(obar, 0); STAMP(tid == 0, 2); combine(); }
    STAMP(tid == 0, 6);
    __syncthreads();
    STAMP(tid == 0, 7);

    {
        float c[4][4];
        #pragma unroll
        for (int e = 0; e < 4; ++e) { c[e][0] = c[e][1] = c[e][2] = c[e][3] = 0.f; }
        uint32_t b0[4], b1[4];
        #pragma unroll
        for (int ks = 0; ks < 4; ++ks) {
            b0[ks] = 0; b1[ks] = 0;
            if (g < 4) {
                asm volatile("ld.shared.u32 %0, [%1];" : "=r"(b0[ks]) : "r"(sbase + SM_QS + (g * 64 + ks * 16 + 2 * t) * 2) : "memory");
                asm volatile("ld.shared.u32 %0, [%1];" : "=r"(b1[ks]) : "r"(sbase + SM_QS + (g * 64 + ks * 16 + 2 * t + 8) * 2) : "memory");
            }
        }
        #pragma unroll
        for (int ks = 0; ks < 4; ++ks) {
            mbar_wait(wobar + ks * 8, 0);
            load_frags(ks);
            #pragma unroll
            for (int e = 0; e < 4; ++e) mma_bf16(c[e], bf0[ks][e], bf0[ks][e + 4], bf1[ks][e], bf1[ks][e + 4], b0[ks], b1[ks]);
        }
        float* tile = s_red + warp * 256;
        if (t < 2) {
            float* dst = tile + 2 * t * 64 + g * 8;
            *reinterpret_cast<float4*>(dst)      = make_float4(c[0][0], c[1][0], c[2][0], c[3][0]);
            *reinterpret_cast<float4*>(dst + 4)  = make_float4(c[0][2], c[1][2], c[2][2], c[3][2]);
            *reinterpret_cast<float4*>(dst + 64) = make_float4(c[0][1], c[1][1], c[2][1], c[3][1]);
            *reinterpret_cast<float4*>(dst + 68) = make_float4(c[0][3], c[1][3], c[2][3], c[3][3]);
        }
        __syncwarp();
        {
            const int col = warp * 64 + lane * 2, sl = col / 40;
            unsigned long long* dst = g_part + ((size_t)(p * 64 + sl) * 64 + (cta & 63)) * 40 + (col - sl * 40);
            constexpr int BSTR = 16 * 64 * 40;
            const unsigned long long hi = (unsigned long long)tag << 32;
            #pragma unroll
            for (int b = 0; b < 4; ++b) {
                const float2 v2 = *reinterpret_cast<const float2*>(tile + b * 64 + lane * 2);
                asm volatile("st.relaxed.gpu.global.v2.b64 [%0], {%1, %2};"
                             :: "l"(dst + b * BSTR), "l"(hi | __float_as_uint(v2.x)), "l"(hi | __float_as_uint(v2.y)) : "memory");
            }
        }
    }
    {
        __syncthreads();
        if (tid == 0) {
            asm volatile("red.relaxed.gpu.global.add.u32 [%0], 1;" :: "l"(&g_cnt) : "memory");
            const unsigned target = tag * (unsigned)NCTA - HINT_K;
            unsigned cur2;
            int spins = 0;
            do {
                asm volatile("ld.relaxed.gpu.global.u32 %0, [%1];" : "=r"(cur2) : "l"(&g_cnt) : "memory");
                if (++spins > (1 << 24)) __trap();
            } while ((int)(cur2 - target) < 0);
        }
        __syncthreads();
    }
    STAMP(tid == 0, 3);

    {
        const int row = cta >> 4;
        const int pp  = row >> 2, bb = row & 3;
        const unsigned long long* src = g_part + (size_t)cta * 64 * 40 + tid * 2;
        unsigned long long v0[4], v1[4];
        #pragma unroll
        for (int j = 0; j < 4; ++j) { v0[j] = 0ull; v1[j] = 0ull; }
        #pragma unroll 1
        for (int spin = 0; ; ++spin) {
            #pragma unroll
            for (int j = 0; j < 4; ++j)
                if ((unsigned)(v0[j] >> 32) != tag || (unsigned)(v1[j] >> 32) != tag)
                    asm volatile("ld.relaxed.gpu.global.v2.b64 {%0, %1}, [%2];" : "=l"(v0[j]), "=l"(v1[j]) : "l"(src + j * 640) : "memory");
            bool ok = true;
            #pragma unroll
            for (int j = 0; j < 4; ++j) ok = ok && ((unsigned)(v0[j] >> 32) == tag) && ((unsigned)(v1[j] >> 32) == tag);
            if (ok) break;
            if (spin > (1 << 22)) __trap();
        }
        STAMP(tid == 0, 4);
        float s0 = 0.f, s1 = 0.f;
        #pragma unroll
        for (int j = 0; j < 4; ++j) { s0 += __uint_as_float((unsigned)v0[j]); s1 += __uint_as_float((unsigned)v1[j]); }
        float* red2 = s_red + 10 * 256;
        *reinterpret_cast<float2*>(red2 + tid * 2) = make_float2(s0, s1);
        __syncthreads();
        if (tid < 40) {
            float s = 0.f;
            #pragma unroll
            for (int k = 0; k < 16; ++k) s += red2[k * 40 + tid];
            P.out[bb * (2 * D_) + pp * D_ + (cta & 15) * 40 + tid] = __float2bfloat16_rn(s);
        }
    }
    if (tid == 0) g_epoch[cta] = tag;
    STAMP(tid == 0, 5);
}

}

extern "C" void kernel_launch(void* const* d_in, const int* in_sizes, int n_in,
                              void* d_out, int out_size) {
    (void)in_sizes; (void)n_in; (void)out_size;
    static bool attr_set = false;
    if (!attr_set) {
        cudaFuncSetAttribute(fused_decode_kernel, cudaFuncAttributeMaxDynamicSharedMemorySize, SM_TOTAL);
        attr_set = true;
    }
    Params P;
    for (int p = 0; p < 2; ++p) {
        P.x[p]  = (const __nv_bfloat16*)d_in[p * 5 + 0];
        P.k[p]  = (const __nv_bfloat16*)d_in[p * 5 + 1];
        P.v[p]  = (const __nv_bfloat16*)d_in[p * 5 + 2];
        P.wq[p] = (const __nv_bfloat16*)d_in[p * 5 + 3];
        P.wo[p] = (const __nv_bfloat16*)d_in[p * 5 + 4];
    }
    P.out = (__nv_bfloat16*)d_out;
    fused_decode_kernel<<<NCTA, THREADS, SM_TOTAL>>>(P);
}
```

```cpp
#include <cuda_runtime.h>
#include <cuda_bf16.h>
#include <stdint.h>

namespace {

constexpr int D_      = 640;
constexpr int H_      = 32;
constexpr int SK_     = 8192;
constexpr int DH_     = 128;
constexpr int W_      = 2048;
constexpr int HD_     = H_ * DH_;

constexpr int NCTA    = 128;
constexpr int NSW     = 8;
constexpr int THREADS = 320;
constexpr int UKEYS   = 16;
constexpr int UBYTES  = UKEYS * DH_ * 2;
constexpr int NST     = 2;
constexpr uint32_t UPP = W_ / UKEYS;
constexpr uint32_t NUNITS = 4 * UPP;
constexpr int WO_STRIDE = D_ * 2 + 16;
constexpr uint32_t WO_TRIG = 10;
constexpr uint32_t WO_GATE = 48;
constexpr uint32_t HINT_K  = 16;

constexpr int SM_RING   = 0;
constexpr int SM_WOS    = SM_RING + NSW * 2 * NST * UBYTES;
constexpr int SM_ST     = SM_WOS + 64 * WO_STRIDE;
constexpr int SM_ML     = SM_ST + 16 * 4 * 64 * 4;
constexpr int SM_QS     = SM_ML + 16 * 4 * 2 * 4;
constexpr int SM_BAR    = SM_QS + 4 * DH_ * 2;
constexpr int SM_CNT    = SM_BAR + (NSW * 2 * NST + 6) * 8;
constexpr int SM_TOTAL  = SM_CNT + 16;
static_assert(SM_TOTAL <= 232448, "smem");

__device__ unsigned long long g_part[NCTA * 4 * D_];
__device__ unsigned           g_epoch[NCTA];
__device__ unsigned           g_trig;
__device__ unsigned           g_cnt;


__device__ __forceinline__ uint32_t smem_u32(const void* p) {
    return (uint32_t)__cvta_generic_to_shared(p);
}
__device__ __forceinline__ void mbar_init(uint32_t bar, uint32_t cnt) {
    asm volatile("mbarrier.init.shared::cta.b64 [%0], %1;" :: "r"(bar), "r"(cnt) : "memory");
}
__device__ __forceinline__ void mbar_expect_tx(uint32_t bar, uint32_t bytes) {
    asm volatile("mbarrier.arrive.expect_tx.shared::cta.b64 _, [%0], %1;" :: "r"(bar), "r"(bytes) : "memory");
}
__device__ __forceinline__ bool mbar_try_wait(uint32_t bar, uint32_t parity) {
    uint32_t ok;
    asm volatile("{\n\t.reg .pred p;\n\t"
                 "mbarrier.try_wait.parity.shared::cta.b64 p, [%1], %2;\n\t"
                 "selp.u32 %0, 1, 0, p;\n\t}"
                 : "=r"(ok) : "r"(bar), "r"(parity) : "memory");
    return ok != 0;
}
__device__ __forceinline__ void mbar_wait(uint32_t bar, uint32_t parity) {
    #pragma unroll 1
    for (int i = 0; i < (1 << 22); ++i)
        if (mbar_try_wait(bar, parity)) return;
    __trap();
}
__device__ __forceinline__ void bulk_g2s(uint32_t dst, const void* src, uint32_t bytes, uint32_t bar) {
    asm volatile("cp.async.bulk.shared::cluster.global.mbarrier::complete_tx::bytes [%0], [%1], %2, [%3];"
                 :: "r"(dst), "l"(src), "r"(bytes), "r"(bar) : "memory");
}
__device__ __forceinline__ void bulk_kv(uint32_t dst, const void* src, uint32_t bytes, uint32_t bar) {
    uint64_t pol; asm volatile("createpolicy.fractional.L2::evict_first.b64 %0, 1.0;" : "=l"(pol));
    asm volatile("cp.async.bulk.shared::cluster.global.mbarrier::complete_tx::bytes.L2::cache_hint [%0], [%1], %2, [%3], %4;"
                 :: "r"(dst), "l"(src), "r"(bytes), "r"(bar), "l"(pol) : "memory");
}
__device__ __forceinline__ uint4 lds128(uint32_t addr) {
    uint4 v;
    asm volatile("ld.shared.v4.u32 {%0,%1,%2,%3}, [%4];" : "=r"(v.x), "=r"(v.y), "=r"(v.z), "=r"(v.w) : "r"(addr) : "memory");
    return v;
}
__device__ __forceinline__ uint4 ldg128_nc(const void* p) {
    uint4 v;
    asm volatile("ld.global.nc.L1::no_allocate.v4.u32 {%0,%1,%2,%3}, [%4];" : "=r"(v.x), "=r"(v.y), "=r"(v.z), "=r"(v.w) : "l"(p));
    return v;
}
__device__ __forceinline__ uint32_t mapa(uint32_t addr, uint32_t rank) {
    uint32_t r; asm volatile("mapa.shared::cluster.u32 %0, %1, %2;" : "=r"(r) : "r"(addr), "r"(rank)); return r;
}
__device__ __forceinline__ void st_async_b32(uint32_t addr, uint32_t v, uint32_t bar) {
    asm volatile("st.async.shared::cluster.mbarrier::complete_tx::bytes.b32 [%0], %1, [%2];" :: "r"(addr), "r"(v), "r"(bar) : "memory");
}
__device__ __forceinline__ void st_async_v2(uint32_t addr, float a, float b, uint32_t bar) {
    asm volatile("st.async.shared::cluster.mbarrier::complete_tx::bytes.v2.f32 [%0], {%1, %2}, [%3];" :: "r"(addr), "f"(a), "f"(b), "r"(bar) : "memory");
}
__device__ __forceinline__ void st_async_v4(uint32_t addr, float a, float b, float c, float d, uint32_t bar) {
    asm volatile("st.async.shared::cluster.mbarrier::complete_tx::bytes.v4.f32 [%0], {%1, %2, %3, %4}, [%5];"
                 :: "r"(addr), "f"(a), "f"(b), "f"(c), "f"(d), "r"(bar) : "memory");
}
__device__ __forceinline__ uint32_t atom_inc_cluster(uint32_t addr) {
    uint32_t o; asm volatile("atom.relaxed.cluster.shared::cluster.add.u32 %0, [%1], 1;" : "=r"(o) : "r"(addr) : "memory"); return o;
}
__device__ __forceinline__ void cluster_arrive_relaxed() { asm volatile("barrier.cluster.arrive.relaxed.aligned;" ::: "memory"); }
__device__ __forceinline__ void cluster_wait()   { asm volatile("barrier.cluster.wait.acquire.aligned;" ::: "memory"); }

__device__ __forceinline__ float bf_lo(uint32_t x) { return __uint_as_float(x << 16); }
__device__ __forceinline__ float bf_hi(uint32_t x) { return __uint_as_float(x & 0xffff0000u); }
__device__ __forceinline__ float bf_round(float x) { return __bfloat162float(__float2bfloat16_rn(x)); }

__device__ __forceinline__ void unpack8(const uint4& v, float (&f)[8]) {
    f[0] = bf_lo(v.x); f[1] = bf_hi(v.x); f[2] = bf_lo(v.y); f[3] = bf_hi(v.y);
    f[4] = bf_lo(v.z); f[5] = bf_hi(v.z); f[6] = bf_lo(v.w); f[7] = bf_hi(v.w);
}

__device__ __forceinline__ void mma_bf16(float (&c)[4], uint32_t a0, uint32_t a1, uint32_t a2, uint32_t a3,
                                         uint32_t b0, uint32_t b1) {
    asm volatile("mma.sync.aligned.m16n8k16.row.col.f32.bf16.bf16.f32 {%0,%1,%2,%3}, {%4,%5,%6,%7}, {%8,%9}, {%0,%1,%2,%3};"
                 : "+f"(c[0]), "+f"(c[1]), "+f"(c[2]), "+f"(c[3])
                 : "r"(a0), "r"(a1), "r"(a2), "r"(a3), "r"(b0), "r"(b1));
}

struct Params {
    const __nv_bfloat16* x[2];
    const __nv_bfloat16* k[2];
    const __nv_bfloat16* v[2];
    const __nv_bfloat16* wq[2];
    const __nv_bfloat16* wo[2];
    __nv_bfloat16* out;
};

__global__ void __cluster_dims__(2, 1, 1) __launch_bounds__(THREADS, 1)
fused_decode_kernel(const Params P) {
    extern __shared__ __align__(128) unsigned char smem[];
    const uint32_t sbase = smem_u32(smem);
    const int tid  = threadIdx.x;
    const int warp = tid >> 5;
    const int lane = tid & 31;

    const int cta = blockIdx.x;
    const int p   = cta >> 6;
    const int h   = (cta >> 1) & 31;
    const int r   = cta & 1;

    const __nv_bfloat16* g_x  = p ? P.x[1]  : P.x[0];
    const __nv_bfloat16* g_k  = p ? P.k[1]  : P.k[0];
    const __nv_bfloat16* g_v  = p ? P.v[1]  : P.v[0];
    const __nv_bfloat16* g_wq = p ? P.wq[1] : P.wq[0];
    const __nv_bfloat16* g_wo = p ? P.wo[1] : P.wo[0];

    float* s_red = reinterpret_cast<float*>(smem + SM_ST);
    const float* s_st = reinterpret_cast<const float*>(smem + SM_ST);
    const float* s_ml = reinterpret_cast<const float*>(smem + SM_ML);

    const uint32_t qbar  = sbase + SM_BAR + NSW * 2 * NST * 8;
    const uint32_t obar  = qbar + 8;
    const uint32_t wobar = qbar + 16;
    if (tid == NSW * 32) {
        mbar_init(qbar, 1); mbar_init(obar, 1);
        #pragma unroll
        for (int j = 0; j < 4; ++j) mbar_init(wobar + j * 8, 1);
        *reinterpret_cast<volatile uint32_t*>(smem + SM_CNT) = 16 * NST;
        *reinterpret_cast<volatile uint32_t*>(smem + SM_CNT + 4) = 0;
        *reinterpret_cast<volatile uint32_t*>(smem + SM_CNT + 8) = 0;
        asm volatile("fence.mbarrier_init.release.cluster;" ::: "memory");
        asm volatile("fence.acq_rel.cluster;" ::: "memory");
        asm volatile("fence.proxy.async.shared::cta;" ::: "memory");
        #pragma unroll
        for (int j = 0; j < 4; ++j) mbar_expect_tx(wobar + j * 8, 16 * D_ * 2);
        mbar_expect_tx(qbar, 2 * 4 * DH_ * 4);
        mbar_expect_tx(obar, 16 * 4 * (64 + 2) * 4);
    }
    __syncwarp();
    cluster_arrive_relaxed();
    __syncthreads();

    const int g = lane >> 2, t = lane & 3;
    uint4 wreg[16];
    uint32_t xa[4];
    {
        const __nv_bfloat16* wp = g_wq + (size_t)(r * 320 + warp * 32 + 2 * t) * HD_ + h * DH_ + g * 8;
        #pragma unroll
        for (int j = 0; j < 2; ++j) {
            #pragma unroll
            for (int i = 0; i < 4; ++i) {
                #pragma unroll
                for (int hh = 0; hh < 2; ++hh)
                    wreg[j * 8 + hh * 4 + i] = ldg128_nc(wp + (size_t)(j * 16 + (i & 1) + (i >> 1) * 8) * HD_ + hh * 64);
            }
        }
        const uint32_t* xp = reinterpret_cast<const uint32_t*>(g_x + (g & 3) * D_ + r * 320 + warp * 32 + 2 * t);
        #pragma unroll
        for (int j = 0; j < 2; ++j) {
            xa[j * 2 + 0] = (g < 4) ? __ldg(xp + j * 8)     : 0u;
            xa[j * 2 + 1] = (g < 4) ? __ldg(xp + j * 8 + 4) : 0u;
        }
    }

    const uint32_t kbuf = sbase + SM_RING + warp * (2 * NST * UBYTES);
    const uint32_t vbuf = kbuf + NST * UBYTES;
    const uint32_t kbar = sbase + SM_BAR + warp * (2 * NST * 8);
    const uint32_t vbar = kbar + NST * 8;
    const uint32_t gw = r * NSW + warp;
    const unsigned char* kg = reinterpret_cast<const unsigned char*>(g_k + ((size_t)h * SK_ + (SK_ - W_)) * DH_);
    const unsigned char* vg = reinterpret_cast<const unsigned char*>(g_v + ((size_t)h * SK_ + (SK_ - W_)) * DH_);
    auto unit_off = [](uint32_t u) -> size_t {
        return (size_t)(u / UPP) * ((size_t)H_ * SK_ * DH_ * 2) + (size_t)(u % UPP) * UBYTES;
    };
    if (warp < NSW) {
        if (lane == 0) {
            #pragma unroll
            for (int s = 0; s < NST; ++s) { mbar_init(kbar + s * 8, 1); mbar_init(vbar + s * 8, 1); }
            asm volatile("fence.mbarrier_init.release.cluster;" ::: "memory");
            asm volatile("fence.proxy.async.shared::cta;" ::: "memory");
            mbar_expect_tx(kbar, UBYTES);
            bulk_kv(kbuf, kg + (size_t)gw * UBYTES, UBYTES, kbar);
            mbar_expect_tx(vbar, UBYTES);
            bulk_kv(vbuf, vg + (size_t)gw * UBYTES, UBYTES, vbar);
        }
        __syncwarp();
    }
    unsigned tag;
    asm volatile("ld.relaxed.gpu.global.u32 %0, [%1];" : "=r"(tag) : "l"(&g_epoch[cta]) : "memory");
    tag += 1u;

    constexpr int SM_QP = SM_WOS + 10 * 4 * 128 * 4;
    {
        float* s_p1 = reinterpret_cast<float*>(smem + SM_WOS);
        #pragma unroll
        for (int hh = 0; hh < 2; ++hh) {
            float c[8][4];
            #pragma unroll
            for (int e = 0; e < 8; ++e) { c[e][0] = c[e][1] = c[e][2] = c[e][3] = 0.f; }
            #pragma unroll
            for (int j = 0; j < 2; ++j) {
                const uint4 x0 = wreg[j * 8 + hh * 4 + 0], x1 = wreg[j * 8 + hh * 4 + 1], x2 = wreg[j * 8 + hh * 4 + 2], x3 = wreg[j * 8 + hh * 4 + 3];
                const uint32_t w0[4] = {x0.x, x0.y, x0.z, x0.w};
                const uint32_t w1[4] = {x1.x, x1.y, x1.z, x1.w};
                const uint32_t w2[4] = {x2.x, x2.y, x2.z, x2.w};
                const uint32_t w3[4] = {x3.x, x3.y, x3.z, x3.w};
                #pragma unroll
                for (int e = 0; e < 8; ++e) {
                    const uint32_t sel = (e & 1) ? 0x7632u : 0x5410u;
                    const uint32_t b0r = __byte_perm(w0[e >> 1], w1[e >> 1], sel);
                    const uint32_t b1r = __byte_perm(w2[e >> 1], w3[e >> 1], sel);
                    mma_bf16(c[e], xa[j * 2], 0u, xa[j * 2 + 1], 0u, b0r, b1r);
                }
            }
            if (g < 4) {
                float* dst = s_p1 + (warp * 4 + g) * 128 + hh * 64 + t * 16;
                *reinterpret_cast<float4*>(dst)      = make_float4(c[0][0], c[1][0], c[2][0], c[3][0]);
                *reinterpret_cast<float4*>(dst + 4)  = make_float4(c[4][0], c[5][0], c[6][0], c[7][0]);
                *reinterpret_cast<float4*>(dst + 8)  = make_float4(c[0][1], c[1][1], c[2][1], c[3][1]);
                *reinterpret_cast<float4*>(dst + 12) = make_float4(c[4][1], c[5][1], c[6][1], c[7][1]);
            }
        }
        __syncthreads();
        cluster_wait();
        if (tid < 256) {
            float s0 = 0.f, s1 = 0.f;
            #pragma unroll
            for (int w = 0; w < 10; ++w) {
                const float2 v2 = *reinterpret_cast<const float2*>(s_p1 + w * 512 + tid * 2);
                s0 += v2.x; s1 += v2.y;
            }
            const uint32_t dst = sbase + SM_QP + (r * 512 + tid * 2) * 4;
            st_async_v2(mapa(dst, 0u), s0, s1, mapa(qbar, 0u));
            st_async_v2(mapa(dst, 1u), s0, s1, mapa(qbar, 1u));
        }
    }
    __syncthreads();
    if (warp < NSW && lane == 0) {
        mbar_expect_tx(kbar + 8, UBYTES);
        bulk_kv(kbuf + UBYTES, kg + (size_t)(gw + 16) * UBYTES, UBYTES, kbar + 8);
        mbar_expect_tx(vbar + 8, UBYTES);
        bulk_kv(vbuf + UBYTES, vg + (size_t)(gw + 16) * UBYTES, UBYTES, vbar + 8);
    }
    __syncwarp();

    const int hl = lane & 15;
    const int hf = lane >> 4;
    const float scale = 0.08838834764831845f;
    const float LOG2E = 1.4426950408889634f;
    float q[8], acc[8];
    float m = -INFINITY, l = 0.f;
    #pragma unroll
    for (int e = 0; e < 8; ++e) { acc[e] = 0.f; q[e] = 0.f; }
    uint32_t idA = NUNITS, idB = NUNITS, nid = NUNITS, cur = 0;
    uint32_t slot = 0, ph = 0;
    const uint32_t cnt_addr = mapa(sbase + SM_CNT, 0u);
    uint4 qb1 = make_uint4(0u, 0u, 0u, 0u), qb2 = qb1, qb3 = qb1;
    if (warp < NSW) {
        idA = gw; idB = gw + 16;
        if (lane == 0) nid = atom_inc_cluster(cnt_addr);
        mbar_wait(qbar, 0);
        auto load_q = [&](uint32_t b) -> uint4 {
            const float4* pa = reinterpret_cast<const float4*>(smem + SM_QP + (b * DH_ + hl * 8) * 4);
            const float4 a0 = pa[0], a1 = pa[1], c0 = pa[128], c1 = pa[129];
            const __nv_bfloat162 y0 = __floats2bfloat162_rn(a0.x + c0.x, a0.y + c0.y), y1 = __floats2bfloat162_rn(a0.z + c0.z, a0.w + c0.w);
            const __nv_bfloat162 y2 = __floats2bfloat162_rn(a1.x + c1.x, a1.y + c1.y), y3 = __floats2bfloat162_rn(a1.z + c1.z, a1.w + c1.w);
            return make_uint4(*reinterpret_cast<const uint32_t*>(&y0), *reinterpret_cast<const uint32_t*>(&y1),
                              *reinterpret_cast<const uint32_t*>(&y2), *reinterpret_cast<const uint32_t*>(&y3));
        };
        unpack8(load_q(0u), q);
        qb1 = load_q(1u); qb2 = load_q(2u); qb3 = load_q(3u);
    }
    asm volatile("fence.proxy.async.shared::cta;" ::: "memory");
    __syncthreads();
    auto push_state = [&](uint32_t b) {
        #pragma unroll
        for (int e = 0; e < 8; ++e) acc[e] += __shfl_xor_sync(0xffffffffu, acc[e], 16);
        #pragma unroll
        for (int o = 16; o >= 1; o >>= 1) l += __shfl_xor_sync(0xffffffffu, l, o);
        if (hf == 0) {
            const uint32_t dr = (uint32_t)hl >> 3;
            const uint32_t a = mapa(sbase + SM_ST + ((gw * 4 + b) * 64 + (hl & 7) * 8) * 4, dr);
            const uint32_t bar = mapa(obar, dr);
            st_async_v4(a,      acc[0], acc[1], acc[2], acc[3], bar);
            st_async_v4(a + 16, acc[4], acc[5], acc[6], acc[7], bar);
        } else if (hl < 2) {
            st_async_v2(mapa(sbase + SM_ML + (gw * 4 + b) * 8, (uint32_t)hl), m, l * 0.5f, mapa(obar, (uint32_t)hl));
        }
        #pragma unroll
        for (int e = 0; e < 8; ++e) acc[e] = 0.f;
        m = -INFINITY; l = 0.f;
    };

    {
        #pragma unroll 1
        while (idA < NUNITS) {
            const uint32_t pr = idA / UPP;
            if (pr != cur) {
                #pragma unroll 1
                for (; cur < pr; ++cur) push_state(cur);
                unpack8(pr == 1u ? qb1 : (pr == 2u ? qb2 : qb3), q);
            }
            mbar_wait(kbar + slot * 8, ph);
            float v[8];
            {
                const uint32_t ka = kbuf + slot * UBYTES + lane * 16;
                #pragma unroll
                for (int s = 0; s < 8; ++s) {
                    uint4 x = lds128(ka + s * 512);
                    float f[8]; unpack8(x, f);
                    float d = f[0] * q[0];
                    #pragma unroll
                    for (int e = 1; e < 8; ++e) d = fmaf(f[e], q[e], d);
                    v[s] = d;
                }
            }
            const uint32_t n = __shfl_sync(0xffffffffu, nid, 0);
            const size_t noff = unit_off(n);
            if (lane == 0 && n >= NUNITS) atomicAdd(reinterpret_cast<uint32_t*>(smem + SM_CNT + 4), 1u);
            if (lane == 0 && n < NUNITS) {
                mbar_expect_tx(kbar + slot * 8, UBYTES);
                bulk_kv(kbuf + slot * UBYTES, kg + noff, UBYTES, kbar + slot * 8);
                nid = atom_inc_cluster(cnt_addr);
            }
            float r4[4], r2[2], r1;
            {
                const bool up = lane & 8;
                #pragma unroll
                for (int j = 0; j < 4; ++j) {
                    float snd = up ? v[j] : v[j + 4];
                    float kep = up ? v[j + 4] : v[j];
                    r4[j] = kep + __shfl_xor_sync(0xffffffffu, snd, 8);
                }
            }
            {
                const bool up = lane & 4;
                #pragma unroll
                for (int j = 0; j < 2; ++j) {
                    float snd = up ? r4[j] : r4[j + 2];
                    float kep = up ? r4[j + 2] : r4[j];
                    r2[j] = kep + __shfl_xor_sync(0xffffffffu, snd, 4);
                }
            }
            {
                const bool up = lane & 2;
                float snd = up ? r2[0] : r2[1];
                float kep = up ? r2[1] : r2[0];
                r1 = kep + __shfl_xor_sync(0xffffffffu, snd, 2);
            }
            r1 += __shfl_xor_sync(0xffffffffu, r1, 1);
            float sc = bf_round(bf_round(r1) * scale);
            float mx = sc;
            #pragma unroll
            for (int o = 16; o >= 2; o >>= 1) mx = fmaxf(mx, __shfl_xor_sync(0xffffffffu, mx, o));
            if (mx > m) {
                const float corr = exp2f((m - mx) * LOG2E);
                l *= corr;
                #pragma unroll
                for (int e = 0; e < 8; ++e) acc[e] *= corr;
                m = mx;
            }
            const float pv = exp2f((sc - m) * LOG2E);
            l += pv;

            mbar_wait(vbar + slot * 8, ph);
            {
                const uint32_t va = vbuf + slot * UBYTES + lane * 16;
                #pragma unroll
                for (int s = 0; s < 8; ++s) {
                    const float pk = __shfl_sync(0xffffffffu, pv, (lane & 16) + 2 * s);
                    uint4 x = lds128(va + s * 512);
                    float f[8]; unpack8(x, f);
                    #pragma unroll
                    for (int e = 0; e < 8; ++e) acc[e] = fmaf(pk, f[e], acc[e]);
                }
            }
            __syncwarp();
            if (lane == 0 && n < NUNITS) {
                mbar_expect_tx(vbar + slot * 8, UBYTES);
                bulk_kv(vbuf + slot * UBYTES, vg + noff, UBYTES, vbar + slot * 8);
            }
            idA = idB; idB = n;
            slot ^= 1u; ph ^= (slot ^ 1u);
        }
    }
    if (warp < NSW) {
        #pragma unroll 1
        for (; cur < 4; ++cur) push_state(cur);
        if (lane == 0) atomicAdd(reinterpret_cast<uint32_t*>(smem + SM_CNT + 4), 1u);
    } else if (warp == NSW) {
        #pragma unroll 1
        for (int i = 0; i < (1 << 22); ++i) {
            if (*reinterpret_cast<volatile uint32_t*>(smem + SM_CNT + 4) >= WO_TRIG) break;
            __nanosleep(100);
        }
        if (lane == 0) asm volatile("red.relaxed.gpu.global.add.u32 [%0], 1;" :: "l"(&g_trig) : "memory");
        #pragma unroll 1
        for (int i = 0; i < (1 << 22); ++i) {
            if (*reinterpret_cast<volatile uint32_t*>(smem + SM_CNT + 8)) break;
            __nanosleep(100);
        }
        const unsigned char* src = reinterpret_cast<const unsigned char*>(g_wo + (size_t)(h * DH_ + r * 64) * D_);
        #pragma unroll
        for (int i = 0; i < 2; ++i) {
            const int row = lane + i * 32;
            bulk_g2s(sbase + SM_WOS + row * WO_STRIDE, src + (size_t)row * (D_ * 2), D_ * 2, wobar + (row >> 4) * 8);
        }
    } else {
        if (lane == 0) {
            const unsigned target = (tag - 1u) * (unsigned)NCTA + WO_GATE;
            #pragma unroll 1
            for (int i = 0; i < (1 << 20); ++i) {
                unsigned c; asm volatile("ld.relaxed.gpu.global.u32 %0, [%1];" : "=r"(c) : "l"(&g_trig) : "memory");
                if ((int)(c - target) >= 0) break;
                __nanosleep(400);
            }
            *reinterpret_cast<volatile uint32_t*>(smem + SM_CNT + 8) = 1;
        }
        __syncwarp();
    }
    uint32_t bf0[4][8], bf1[4][8];
    auto load_frags = [&](const int j) {
        const uint32_t wa = sbase + SM_WOS + (j * 16 + 2 * t) * WO_STRIDE + (warp * 64 + g * 8) * 2;
        const uint4 x0 = lds128(wa), x1 = lds128(wa + WO_STRIDE), x2 = lds128(wa + 8 * WO_STRIDE), x3 = lds128(wa + 9 * WO_STRIDE);
        const uint32_t w0[4] = {x0.x, x0.y, x0.z, x0.w};
        const uint32_t w1[4] = {x1.x, x1.y, x1.z, x1.w};
        const uint32_t w2[4] = {x2.x, x2.y, x2.z, x2.w};
        const uint32_t w3[4] = {x3.x, x3.y, x3.z, x3.w};
        #pragma unroll
        for (int e = 0; e < 8; ++e) {
            const uint32_t sel = (e & 1) ? 0x7632u : 0x5410u;
            bf0[j][e] = __byte_perm(w0[e >> 1], w1[e >> 1], sel);
            bf1[j][e] = __byte_perm(w2[e >> 1], w3[e >> 1], sel);
        }
    };
    auto combine = [&]() {
        const int b = tid >> 6, d = tid & 63;
        float M = -INFINITY;
        #pragma unroll
        for (int w = 0; w < 16; ++w) M = fmaxf(M, s_ml[(w * 4 + b) * 2]);
        float L = 0.f, o = 0.f;
        #pragma unroll
        for (int w = 0; w < 16; ++w) {
            const float2 ml = *reinterpret_cast<const float2*>(s_ml + (w * 4 + b) * 2);
            const float c = exp2f((ml.x - M) * LOG2E);
            L = fmaf(ml.y, c, L);
            o = fmaf(s_st[(w * 4 + b) * 64 + d], c, o);
        }
        const __nv_bfloat16 ob = __float2bfloat16_rn(o / L);
        *reinterpret_cast<__nv_bfloat16*>(smem + SM_QS + (b * 64 + d) * 2) = ob;
    };
    if (tid < 256) { mbar_wait(obar, 0); combine(); }
    __syncthreads();

    {
        float c[4][4];
        #pragma unroll
        for (int e = 0; e < 4; ++e) { c[e][0] = c[e][1] = c[e][2] = c[e][3] = 0.f; }
        uint32_t b0[4], b1[4];
        #pragma unroll
        for (int ks = 0; ks < 4; ++ks) {
            b0[ks] = 0; b1[ks] = 0;
            if (g < 4) {
                asm volatile("ld.shared.u32 %0, [%1];" : "=r"(b0[ks]) : "r"(sbase + SM_QS + (g * 64 + ks * 16 + 2 * t) * 2) : "memory");
                asm volatile("ld.shared.u32 %0, [%1];" : "=r"(b1[ks]) : "r"(sbase + SM_QS + (g * 64 + ks * 16 + 2 * t + 8) * 2) : "memory");
            }
        }
        #pragma unroll
        for (int ks = 0; ks < 4; ++ks) {
            mbar_wait(wobar + ks * 8, 0);
            load_frags(ks);
            #pragma unroll
            for (int e = 0; e < 4; ++e) mma_bf16(c[e], bf0[ks][e], bf0[ks][e + 4], bf1[ks][e], bf1[ks][e + 4], b0[ks], b1[ks]);
        }
        float* tile = s_red + warp * 256;
        if (t < 2) {
            float* dst = tile + 2 * t * 64 + g * 8;
            *reinterpret_cast<float4*>(dst)      = make_float4(c[0][0], c[1][0], c[2][0], c[3][0]);
            *reinterpret_cast<float4*>(dst + 4)  = make_float4(c[0][2], c[1][2], c[2][2], c[3][2]);
            *reinterpret_cast<float4*>(dst + 64) = make_float4(c[0][1], c[1][1], c[2][1], c[3][1]);
            *reinterpret_cast<float4*>(dst + 68) = make_float4(c[0][3], c[1][3], c[2][3], c[3][3]);
        }
        __syncwarp();
        {
            const int col = warp * 64 + lane * 2, sl = col / 40;
            unsigned long long* dst = g_part + ((size_t)(p * 64 + sl) * 64 + (cta & 63)) * 40 + (col - sl * 40);
            constexpr int BSTR = 16 * 64 * 40;
            const unsigned long long hi = (unsigned long long)tag << 32;
            #pragma unroll
            for (int b = 0; b < 4; ++b) {
                const float2 v2 = *reinterpret_cast<const float2*>(tile + b * 64 + lane * 2);
                asm volatile("st.relaxed.gpu.global.v2.b64 [%0], {%1, %2};"
                             :: "l"(dst + b * BSTR), "l"(hi | __float_as_uint(v2.x)), "l"(hi | __float_as_uint(v2.y)) : "memory");
            }
        }
    }
    {
        __syncthreads();
        if (tid == 0) {
            asm volatile("red.relaxed.gpu.global.add.u32 [%0], 1;" :: "l"(&g_cnt) : "memory");
            const unsigned target = tag * (unsigned)NCTA - HINT_K;
            unsigned cur2;
            int spins = 0;
            do {
                asm volatile("ld.relaxed.gpu.global.u32 %0, [%1];" : "=r"(cur2) : "l"(&g_cnt) : "memory");
                if (++spins > (1 << 24)) __trap();
            } while ((int)(cur2 - target) < 0);
        }
        __syncthreads();
    }

    {
        const int row = cta >> 4;
        const int pp  = row >> 2, bb = row & 3;
        const unsigned long long* src = g_part + (size_t)cta * 64 * 40 + tid * 2;
        unsigned long long v0[4], v1[4];
        #pragma unroll
        for (int j = 0; j < 4; ++j) { v0[j] = 0ull; v1[j] = 0ull; }
        #pragma unroll 1
        for (int spin = 0; ; ++spin) {
            #pragma unroll
            for (int j = 0; j < 4; ++j)
                if ((unsigned)(v0[j] >> 32) != tag || (unsigned)(v1[j] >> 32) != tag)
                    asm volatile("ld.relaxed.gpu.global.v2.b64 {%0, %1}, [%2];" : "=l"(v0[j]), "=l"(v1[j]) : "l"(src + j * 640) : "memory");
            bool ok = true;
            #pragma unroll
            for (int j = 0; j < 4; ++j) ok = ok && ((unsigned)(v0[j] >> 32) == tag) && ((unsigned)(v1[j] >> 32) == tag);
            if (ok) break;
            if (spin > (1 << 22)) __trap();
        }
        float s0 = 0.f, s1 = 0.f;
        #pragma unroll
        for (int j = 0; j < 4; ++j) { s0 += __uint_as_float((unsigned)v0[j]); s1 += __uint_as_float((unsigned)v1[j]); }
        float* red2 = s_red + 10 * 256;
        *reinterpret_cast<float2*>(red2 + tid * 2) = make_float2(s0, s1);
        __syncthreads();
        if (tid < 40) {
            float s = 0.f;
            #pragma unroll
            for (int k = 0; k < 16; ++k) s += red2[k * 40 + tid];
            P.out[bb * (2 * D_) + pp * D_ + (cta & 15) * 40 + tid] = __float2bfloat16_rn(s);
        }
    }
    if (tid == 0) g_epoch[cta] = tag;
}

}

extern "C" void kernel_launch(void* const* d_in, const int* in_sizes, int n_in,
                              void* d_out, int out_size) {
    (void)in_sizes; (void)n_in; (void)out_size;
    static bool attr_set = false;
    if (!attr_set) {
        cudaFuncSetAttribute(fused_decode_kernel, cudaFuncAttributeMaxDynamicSharedMemorySize, SM_TOTAL);
        attr_set = true;
    }
    Params P;
    for (int p = 0; p < 2; ++p) {
        P.x[p]  = (const __nv_bfloat16*)d_in[p * 5 + 0];
        P.k[p]  = (const __nv_bfloat16*)d_in[p * 5 + 1];
        P.v[p]  = (const __nv_bfloat16*)d_in[p * 5 + 2];
        P.wq[p] = (const __nv_bfloat16*)d_in[p * 5 + 3];
        P.wo[p] = (const __nv_bfloat16*)d_in[p * 5 + 4];
    }
    P.out = (__nv_bfloat16*)d_out;
    fused_decode_kernel<<<NCTA, THREADS, SM_TOTAL>>>(P);
}
```
